```python
import torch

def _softmax(x, axis=-1):
    return torch.softmax(x, dim=axis)
def _gelu(x):
    return torch.nn.functional.gelu(x, approximate="tanh")
def _silu(x):
    return torch.nn.functional.silu(x)
def _sigmoid(x):
    return torch.sigmoid(x)
def _layernorm(x, axis=-1, eps=1e-5):
    m = x.mean(dim=axis, keepdim=True)
    v = x.var(dim=axis, keepdim=True, unbiased=False)
    return (x - m) / torch.sqrt(v + eps)
def _scatter_add(tgt, idx, src, axis=0):
    return tgt.clone().index_add_(axis, idx, src)
def _segment_sum(src, seg, n):
    out = torch.zeros((n,) + src.shape[1:], dtype=src.dtype)
    return out.index_add_(0, seg, src)
def _pad(x, pw):
    flat = tuple(v for pair in reversed(pw) for v in pair)
    return torch.nn.functional.pad(x, flat)

kernel_name = 'sequential_preLN__sliding_local_dilated__dense_activation_relu__prompt'

def setup_inputs():

    _w = (lambda a: (lambda t: t.to(torch.bfloat16) if t.is_floating_point() else t)(torch.as_tensor(a)))
    def _A_setup():
        B, S, D = 1, 2048, 448
        return {
            "x": _w((lambda *s: torch.randn(*s, dtype=torch.bfloat16) * 0.05)(B, S, D)),
            "wqkv": _w((lambda *s: torch.randn(*s, dtype=torch.bfloat16) * 0.05)(D, 3 * D)),
            "wo": _w((lambda *s: torch.randn(*s, dtype=torch.bfloat16) * 0.05)(D, D)),
        }
    _A_in = _A_setup()

    def _B_setup():
        B, S, D, Dff = 1, 2048, 448, 1792
        return {
            "x": _w((lambda *s: torch.randn(*s, dtype=torch.bfloat16) * 0.05)(B, S, D)),
            "w1": _w((lambda *s: torch.randn(*s, dtype=torch.bfloat16) * 0.05)(D, Dff)),
            "w2": _w((lambda *s: torch.randn(*s, dtype=torch.bfloat16) * 0.05)(Dff, D)),
        }
    _B_in = _B_setup()

    return {
        "A_x": _A_in["x"],
        "A_wqkv": _A_in["wqkv"],
        "A_wo": _A_in["wo"],
        "B_x": _B_in["x"],
        "B_w1": _B_in["w1"],
        "B_w2": _B_in["w2"],
    }

def reference(A_x, A_wqkv, A_wo, B_x, B_w1, B_w2):
    def _A_ref(x, wqkv, wo):
        B, S, D = x.shape
        H = 16; Dh = D // H
        W, dil = 8, 2
        qkv = (lambda x, *d: x.permute(*d))((x @ wqkv).reshape(B, S, 3, H, Dh), 2, 0, 3, 1, 4)
        q, k, v = qkv[0], qkv[1], qkv[2]
        scale = Dh ** -0.5
        pos = torch.arange(S)
        off = torch.arange(W) * dil
        idx = pos[:, None] - off[None, :]
        mask = idx >= 0
        idx_c = torch.where(mask, idx, 0).reshape(-1)
        kg = k[:, :, idx_c, :].reshape(B, H, S, W, Dh)
        vg = v[:, :, idx_c, :].reshape(B, H, S, W, Dh)
        logits = torch.einsum("bhsd,bhswd->bhsw", q, kg) * scale
        logits = torch.where(mask[None, None, :, :], logits, -1e9)
        attn = _softmax(logits, axis=-1)
        o = torch.einsum("bhsw,bhswd->bhsd", attn, vg)
        return (lambda x, *d: x.permute(*d))(o, 0, 2, 1, 3).reshape(B, S, D) @ wo

    def _B_ref(x, w1, w2):
        h = torch.einsum("bsd,df->bsf", x, w1)
        zero = torch.zeros_like(h)
        h = torch.maximum(h, zero)
        return torch.einsum("bsf,fd->bsd", h, w2)

    x = A_x
    h = x + _A_ref(_layernorm(x, axis=-1), A_wqkv, A_wo)
    h2 = h + _B_ref(_layernorm(h, axis=-1), B_w1, B_w2)
    return h2
```

```cpp
#include <cuda_runtime.h>
#include <cuda_bf16.h>
#include <cuda.h>
#include <stdint.h>

#define USE_MC 1
#define NO_PREFETCH 1
#define PF_STAGE 0
#define MAPPING 2
#define CLEAR_STAGE 4
#define GATE_A_STAGE -1
#define GATE_A_BAR 18
#define GATE_B_STAGE -1
#define GATE_B_BAR 19
#define PF_START 0
#define HALO_HINT 1
#define HALO_EARLY 1
#define PINGPONG 1

namespace {

constexpr int SEQ = 2048;
constexpr int DM = 448;
constexpr int DFF = 1792;
constexpr int TILE_B = 14336;
constexpr int STAGE_B = 2 * TILE_B;
constexpr int NST = 8;
constexpr int NSTAGE_TOTAL = 27;
__host__ __device__ constexpr int slot_of(int i) {
  return i < 4 ? (i & 1) : i < 8 ? i : i < 10 ? i - 6 : i == 10 ? 0 : "\4\5\6\7\2\3\0\1"[(i - 11) & 7];
}
__host__ __device__ constexpr int use_of(int i) {
  return i < 2 ? 0 : i < 4 ? 1 : i < 10 ? 0 : i == 10 ? 2 : (slot_of(i) < 2 ? 2 : 0) + 1 + (i - 11) / 8;
}
__host__ __device__ constexpr int full_bar(int i) { return i == 2 ? 22 : i == 3 ? 23 : slot_of(i); }
__host__ __device__ constexpr int full_par(int i) {
  return (i == 2 || i == 3) ? 0 : (slot_of(i) == 0 && i >= 10) ? (use_of(i) - 1) & 1 : (slot_of(i) == 1 && i >= 10) ? (use_of(i) - 2) & 1 : use_of(i) & 1;
}
__host__ __device__ constexpr int stage_bytes(int i) {
  return i < 4 ? 28672 : i < 12 ? 2 * 112 * 112 : (i >= 16 && i < 20) ? 112 * (128 + 64) : 28672;
}
constexpr int HAND_SLOT = 1;
constexpr int HAND_OFF = HAND_SLOT * STAGE_B;
constexpr int ZERO_OFF = NST * STAGE_B;
constexpr int ZERO_B = 2048;
constexpr int BAR_OFF = ZERO_OFF + ZERO_B;
constexpr int SMEM_B = BAR_OFF + 256;
constexpr int NTHREADS = 384;
constexpr uint32_t SPIN_LIMIT = 1u << 20;

__device__ uint4 g_O[2][128 * 8 * 112];
__device__ uint4 g_H[2][128 * 8 * 120];
__device__ uint4 g_halo[2][16 * 2 * 8 * 128];
__device__ uint4 g_P[128 * 8 * 896];
__device__ uint32_t g_sync[128 * 64];
constexpr int SY_O = 0, SY_H = 8, SY_P0 = 16, SY_EPOCH = 24, SY_EPOCH2 = 32, SY_P1 = 40, SY_P2 = 48, SY_P3 = 56;

#define TS(i) do {} while (0)
#define TS2(i) do {} while (0)
#define XTS(i) do {} while (0)
#define TTS(i) do {} while (0)
#define PROBE(i) do {} while (0)

__device__ __forceinline__ uint32_t smem_u32(const void* p) { return (uint32_t)__cvta_generic_to_shared(p); }

__device__ __forceinline__ void mbar_init(uint32_t bar, uint32_t cnt) {
  asm volatile("mbarrier.init.shared::cta.b64 [%0], %1;" ::"r"(bar), "r"(cnt) : "memory");
}
__device__ __forceinline__ void mbar_expect_tx(uint32_t bar, uint32_t bytes) {
  asm volatile("mbarrier.arrive.expect_tx.shared::cta.b64 _, [%0], %1;" ::"r"(bar), "r"(bytes) : "memory");
}
__device__ __forceinline__ void mbar_arrive(uint32_t bar, uint32_t cnt) {
  asm volatile("mbarrier.arrive.shared::cta.b64 _, [%0], %1;" ::"r"(bar), "r"(cnt) : "memory");
}
__device__ __forceinline__ void mbar_arrive_cluster(uint32_t bar, uint32_t cta, uint32_t cnt) {
  asm volatile(
      "{\n.reg .b32 ra;\nmapa.shared::cluster.u32 ra, %0, %1;\n"
      "mbarrier.arrive.shared::cluster.b64 _, [ra], %2;\n}" ::"r"(bar), "r"(cta), "r"(cnt)
      : "memory");
}
__device__ __forceinline__ bool mbar_try(uint32_t bar, uint32_t parity) {
  uint32_t ok;
  asm volatile(
      "{\n.reg .pred p;\nmbarrier.try_wait.parity.shared::cta.b64 p, [%1], %2;\nselp.u32 %0, 1, 0, p;\n}"
      : "=r"(ok)
      : "r"(bar), "r"(parity)
      : "memory");
  return ok != 0;
}
__device__ __forceinline__ void mbar_wait(uint32_t bar, uint32_t parity) {
  for (uint32_t it = 0; !mbar_try(bar, parity) && it < SPIN_LIMIT; it++) {}
}

template <int DIM>
__device__ __forceinline__ void tma_load(uint32_t dst, const CUtensorMap* tm, uint32_t bar, int c0, int c1, int c2, int c3) {
  uint64_t d = reinterpret_cast<uint64_t>(tm);
  if constexpr (DIM == 2)
    asm volatile("cp.async.bulk.tensor.2d.shared::cluster.global.mbarrier::complete_tx::bytes [%0], [%1, {%3, %4}], [%2];" ::"r"(dst),
                 "l"(d), "r"(bar), "r"(c0), "r"(c1)
                 : "memory");
  if constexpr (DIM == 3)
    asm volatile("cp.async.bulk.tensor.3d.shared::cluster.global.mbarrier::complete_tx::bytes [%0], [%1, {%3, %4, %5}], [%2];" ::"r"(dst),
                 "l"(d), "r"(bar), "r"(c0), "r"(c1), "r"(c2)
                 : "memory");
  if constexpr (DIM == 4)
    asm volatile("cp.async.bulk.tensor.4d.shared::cluster.global.mbarrier::complete_tx::bytes [%0], [%1, {%3, %4, %5, %6}], [%2];" ::"r"(dst),
                 "l"(d), "r"(bar), "r"(c0), "r"(c1), "r"(c2), "r"(c3)
                 : "memory");
}
template <int DIM>
__device__ __forceinline__ void tma_load_mc(uint32_t dst, const CUtensorMap* tm, uint32_t bar, int c0, int c1, int c2) {
  uint64_t d = reinterpret_cast<uint64_t>(tm);
  const uint16_t mask = 3;
  if constexpr (DIM == 2)
    asm volatile(
        "cp.async.bulk.tensor.2d.shared::cluster.global.mbarrier::complete_tx::bytes.multicast::cluster [%0], [%1, {%3, %4}], [%2], %5;" ::"r"(dst),
        "l"(d), "r"(bar), "r"(c0), "r"(c1), "h"(mask)
        : "memory");
  if constexpr (DIM == 3)
    asm volatile(
        "cp.async.bulk.tensor.3d.shared::cluster.global.mbarrier::complete_tx::bytes.multicast::cluster [%0], [%1, {%3, %4, %5}], [%2], %6;" ::"r"(dst),
        "l"(d), "r"(bar), "r"(c0), "r"(c1), "r"(c2), "h"(mask)
        : "memory");
}
__device__ __forceinline__ void bulk_store(void* dst, uint32_t src, uint32_t bytes) {
  asm volatile("cp.async.bulk.global.shared::cta.bulk_group [%0], [%1], %2;" ::"l"(dst), "r"(src), "r"(bytes) : "memory");
}

__device__ __forceinline__ uint4 ldx16(const void* p) {
  uint4 v;
  asm volatile(
      "{\n.reg .b128 t;\n.reg .b64 lo, hi;\nld.relaxed.gpu.global.b128 t, [%4];\nmov.b128 {lo, hi}, t;\n"
      "mov.b64 {%0, %1}, lo;\nmov.b64 {%2, %3}, hi;\n}"
      : "=r"(v.x), "=r"(v.y), "=r"(v.z), "=r"(v.w)
      : "l"(p)
      : "memory");
  return v;
}
__device__ __forceinline__ void stx16(void* p, uint32_t a, uint32_t b, uint32_t c, uint32_t d) {
  asm volatile(
      "{\n.reg .b128 t;\n.reg .b64 lo, hi;\nmov.b64 lo, {%1, %2};\nmov.b64 hi, {%3, %4};\nmov.b128 t, {lo, hi};\n"
      "st.relaxed.gpu.global.b128 [%0], t;\n}" ::"l"(p),
      "r"(a), "r"(b), "r"(c), "r"(d)
      : "memory");
}
__device__ __forceinline__ uint2 ldx8(const void* p) {
  uint2 v;
  asm volatile("{\n.reg .b64 t;\nld.relaxed.gpu.global.b64 t, [%2];\nmov.b64 {%0, %1}, t;\n}" : "=r"(v.x), "=r"(v.y) : "l"(p) : "memory");
  return v;
}
__device__ __forceinline__ void stx8(void* p, uint32_t a, uint32_t b) {
  asm volatile("{\n.reg .b64 t;\nmov.b64 t, {%1, %2};\nst.relaxed.gpu.global.b64 [%0], t;\n}" ::"l"(p), "r"(a), "r"(b) : "memory");
}
__device__ __forceinline__ uint32_t nz(uint32_t w) { return max(w, 1u); }
__device__ __forceinline__ bool spin_expired(uint32_t& it) { return ++it > SPIN_LIMIT; }

__device__ __forceinline__ uint32_t pack_bf16(float lo, float hi) {
  uint32_t r;
  asm("cvt.rn.bf16x2.f32 %0, %1, %2;" : "=r"(r) : "f"(hi), "f"(lo));
  return r;
}
__device__ __forceinline__ uint32_t pack_bf16_relu(float lo, float hi) {
  uint32_t r;
  asm("cvt.rn.relu.bf16x2.f32 %0, %1, %2;" : "=r"(r) : "f"(hi), "f"(lo));
  return r;
}
__device__ __forceinline__ float bf_lo(uint32_t w) { return __uint_as_float(w << 16); }
__device__ __forceinline__ float bf_hi(uint32_t w) { return __uint_as_float(w & 0xffff0000u); }
__device__ __forceinline__ uint32_t bf2_sub(uint32_t a, uint32_t b) {
  uint32_t r;
  asm("sub.rn.bf16x2 %0, %1, %2;" : "=r"(r) : "r"(a), "r"(b));
  return r;
}
__device__ __forceinline__ uint32_t bf2_add(uint32_t a, uint32_t b) {
  uint32_t r;
  asm("add.rn.bf16x2 %0, %1, %2;" : "=r"(r) : "r"(a), "r"(b));
  return r;
}
__device__ __forceinline__ void mma16816(float (&d)[4], uint32_t a0, uint32_t a1, uint32_t a2, uint32_t a3, uint32_t b0, uint32_t b1) {
  asm("mma.sync.aligned.m16n8k16.row.col.f32.bf16.bf16.f32 {%0,%1,%2,%3}, {%4,%5,%6,%7}, {%8,%9}, {%0,%1,%2,%3};"
      : "+f"(d[0]), "+f"(d[1]), "+f"(d[2]), "+f"(d[3])
      : "r"(a0), "r"(a1), "r"(a2), "r"(a3), "r"(b0), "r"(b1));
}
__device__ __forceinline__ void mma1688(float (&d)[4], uint32_t a0, uint32_t a1, uint32_t b0) {
  asm("mma.sync.aligned.m16n8k8.row.col.f32.bf16.bf16.f32 {%0,%1,%2,%3}, {%4,%5}, {%6}, {%0,%1,%2,%3};"
      : "+f"(d[0]), "+f"(d[1]), "+f"(d[2]), "+f"(d[3])
      : "r"(a0), "r"(a1), "r"(b0));
}
__device__ __forceinline__ uint32_t movmat(uint32_t a) {
  uint32_t d;
  asm volatile("movmatrix.sync.aligned.m8n8.trans.b16 %0, %1;" : "=r"(d) : "r"(a));
  return d;
}
__device__ __forceinline__ float ex2(float x) {
  float y;
  asm("ex2.approx.ftz.f32 %0, %1;" : "=f"(y) : "f"(x));
  return y;
}

__device__ __forceinline__ float rcp(float x) {
  float y;
  asm("rcp.approx.ftz.f32 %0, %1;" : "=f"(y) : "f"(x));
  return y;
}

__device__ __forceinline__ void wg_fence() { asm volatile("wgmma.fence.sync.aligned;" ::: "memory"); }
__device__ __forceinline__ void wg_commit() { asm volatile("wgmma.commit_group.sync.aligned;" ::: "memory"); }
template <int N>
__device__ __forceinline__ void wg_wait() {
  asm volatile("wgmma.wait_group.sync.aligned %0;" ::"n"(N) : "memory");
}
template <int N>
__device__ __forceinline__ void reg_fence(float (&d)[N]) {
#pragma unroll
  for (int i = 0; i < N; i++) asm volatile("" : "+f"(d[i])::"memory");
}

__device__ __forceinline__ uint32_t opaque(uint32_t v) {
  uint32_t r;
  asm volatile("mov.u32 %0, %1;" : "=r"(r) : "r"(v));
  return r;
}

constexpr uint32_t DESC_LBO = (uint32_t)(TILE_B >> 4) << 16;
constexpr uint32_t DESC_HI = (1024u >> 4) | (1u << 30);
constexpr uint32_t DESC_HI_FAR = (7168u >> 4) | (1u << 30);

#define WG_ACC4(d, i) "+f"(d[i]), "+f"(d[i + 1]), "+f"(d[i + 2]), "+f"(d[i + 3])
#define WG_OUT4(d, i) "=f"(d[i]), "=f"(d[i + 1]), "=f"(d[i + 2]), "=f"(d[i + 3])

__device__ __forceinline__ void wgmma_n56(float (&d)[28], uint32_t a0, uint32_t a1, uint32_t a2, uint32_t a3, uint32_t lo, uint32_t hi) {
  asm volatile(
      "{\n.reg .b64 dsc;\n.reg .pred p;\n"
      "mov.b64 dsc, {%32, %33};\nsetp.ne.b32 p, 1, 0;\n"
      "wgmma.mma_async.sync.aligned.m64n56k16.f32.bf16.bf16 "
      "{%0, %1, %2, %3, %4, %5, %6, %7, %8, %9, %10, %11, %12, %13, %14, %15, "
      "%16, %17, %18, %19, %20, %21, %22, %23, %24, %25, %26, %27}, "
      "{%28, %29, %30, %31}, dsc, p, 1, 1, 1;\n}"
      : WG_ACC4(d, 0), WG_ACC4(d, 4), WG_ACC4(d, 8), WG_ACC4(d, 12), WG_ACC4(d, 16), WG_ACC4(d, 20), WG_ACC4(d, 24)
      : "r"(a0), "r"(a1), "r"(a2), "r"(a3), "r"(lo), "r"(hi));
}
__device__ __forceinline__ void wgmma_n56_init(float (&d)[28], uint32_t a0, uint32_t a1, uint32_t a2, uint32_t a3, uint32_t lo, uint32_t hi) {
  asm volatile(
      "{\n.reg .b64 dsc;\n.reg .pred p;\n"
      "mov.b64 dsc, {%32, %33};\nsetp.ne.b32 p, 0, 0;\n"
      "wgmma.mma_async.sync.aligned.m64n56k16.f32.bf16.bf16 "
      "{%0, %1, %2, %3, %4, %5, %6, %7, %8, %9, %10, %11, %12, %13, %14, %15, "
      "%16, %17, %18, %19, %20, %21, %22, %23, %24, %25, %26, %27}, "
      "{%28, %29, %30, %31}, dsc, p, 1, 1, 1;\n}"
      : WG_OUT4(d, 0), WG_OUT4(d, 4), WG_OUT4(d, 8), WG_OUT4(d, 12), WG_OUT4(d, 16), WG_OUT4(d, 20), WG_OUT4(d, 24)
      : "r"(a0), "r"(a1), "r"(a2), "r"(a3), "r"(lo), "r"(hi));
}
__device__ __forceinline__ void wgmma_n64(float (&d)[32], uint32_t a0, uint32_t a1, uint32_t a2, uint32_t a3, uint32_t lo, uint32_t hi) {
  asm volatile(
      "{\n.reg .b64 dsc;\n.reg .pred p;\n"
      "mov.b64 dsc, {%36, %37};\nsetp.ne.b32 p, 1, 0;\n"
      "wgmma.mma_async.sync.aligned.m64n64k16.f32.bf16.bf16 "
      "{%0, %1, %2, %3, %4, %5, %6, %7, %8, %9, %10, %11, %12, %13, %14, %15, "
      "%16, %17, %18, %19, %20, %21, %22, %23, %24, %25, %26, %27, %28, %29, %30, %31}, "
      "{%32, %33, %34, %35}, dsc, p, 1, 1, 1;\n}"
      : WG_ACC4(d, 0), WG_ACC4(d, 4), WG_ACC4(d, 8), WG_ACC4(d, 12), WG_ACC4(d, 16), WG_ACC4(d, 20), WG_ACC4(d, 24), WG_ACC4(d, 28)
      : "r"(a0), "r"(a1), "r"(a2), "r"(a3), "r"(lo), "r"(hi));
}
__device__ __forceinline__ void wgmma_n64_init(float (&d)[32], uint32_t a0, uint32_t a1, uint32_t a2, uint32_t a3, uint32_t lo, uint32_t hi) {
  asm volatile(
      "{\n.reg .b64 dsc;\n.reg .pred p;\n"
      "mov.b64 dsc, {%36, %37};\nsetp.ne.b32 p, 0, 0;\n"
      "wgmma.mma_async.sync.aligned.m64n64k16.f32.bf16.bf16 "
      "{%0, %1, %2, %3, %4, %5, %6, %7, %8, %9, %10, %11, %12, %13, %14, %15, "
      "%16, %17, %18, %19, %20, %21, %22, %23, %24, %25, %26, %27, %28, %29, %30, %31}, "
      "{%32, %33, %34, %35}, dsc, p, 1, 1, 1;\n}"
      : WG_OUT4(d, 0), WG_OUT4(d, 4), WG_OUT4(d, 8), WG_OUT4(d, 12), WG_OUT4(d, 16), WG_OUT4(d, 20), WG_OUT4(d, 24), WG_OUT4(d, 28)
      : "r"(a0), "r"(a1), "r"(a2), "r"(a3), "r"(lo), "r"(hi));
}
__device__ __forceinline__ void wgmma_n96(float (&d)[48], uint32_t a0, uint32_t a1, uint32_t a2, uint32_t a3, uint32_t lo, uint32_t hi) {
  asm volatile(
      "{\n.reg .b64 dsc;\n.reg .pred p;\n"
      "mov.b64 dsc, {%52, %53};\nsetp.ne.b32 p, 1, 0;\n"
      "wgmma.mma_async.sync.aligned.m64n96k16.f32.bf16.bf16 "
      "{%0, %1, %2, %3, %4, %5, %6, %7, %8, %9, %10, %11, %12, %13, %14, %15, "
      "%16, %17, %18, %19, %20, %21, %22, %23, %24, %25, %26, %27, %28, %29, %30, %31, "
      "%32, %33, %34, %35, %36, %37, %38, %39, %40, %41, %42, %43, %44, %45, %46, %47}, "
      "{%48, %49, %50, %51}, dsc, p, 1, 1, 1;\n}"
      : WG_ACC4(d, 0), WG_ACC4(d, 4), WG_ACC4(d, 8), WG_ACC4(d, 12), WG_ACC4(d, 16), WG_ACC4(d, 20), WG_ACC4(d, 24), WG_ACC4(d, 28), WG_ACC4(d, 32), WG_ACC4(d, 36), WG_ACC4(d, 40), WG_ACC4(d, 44)
      : "r"(a0), "r"(a1), "r"(a2), "r"(a3), "r"(lo), "r"(hi));
}
__device__ __forceinline__ void wgmma_n96_init(float (&d)[48], uint32_t a0, uint32_t a1, uint32_t a2, uint32_t a3, uint32_t lo, uint32_t hi) {
  asm volatile(
      "{\n.reg .b64 dsc;\n.reg .pred p;\n"
      "mov.b64 dsc, {%52, %53};\nsetp.ne.b32 p, 0, 0;\n"
      "wgmma.mma_async.sync.aligned.m64n96k16.f32.bf16.bf16 "
      "{%0, %1, %2, %3, %4, %5, %6, %7, %8, %9, %10, %11, %12, %13, %14, %15, "
      "%16, %17, %18, %19, %20, %21, %22, %23, %24, %25, %26, %27, %28, %29, %30, %31, "
      "%32, %33, %34, %35, %36, %37, %38, %39, %40, %41, %42, %43, %44, %45, %46, %47}, "
      "{%48, %49, %50, %51}, dsc, p, 1, 1, 1;\n}"
      : WG_OUT4(d, 0), WG_OUT4(d, 4), WG_OUT4(d, 8), WG_OUT4(d, 12), WG_OUT4(d, 16), WG_OUT4(d, 20), WG_OUT4(d, 24), WG_OUT4(d, 28), WG_OUT4(d, 32), WG_OUT4(d, 36), WG_OUT4(d, 40), WG_OUT4(d, 44)
      : "r"(a0), "r"(a1), "r"(a2), "r"(a3), "r"(lo), "r"(hi));
}
__device__ __forceinline__ void wgmma_n120(float (&d)[60], uint32_t a0, uint32_t a1, uint32_t a2, uint32_t a3, uint32_t lo, uint32_t hi) {
  asm volatile(
      "{\n.reg .b64 dsc;\n.reg .pred p;\n"
      "mov.b64 dsc, {%64, %65};\nsetp.ne.b32 p, 1, 0;\n"
      "wgmma.mma_async.sync.aligned.m64n120k16.f32.bf16.bf16 "
      "{%0, %1, %2, %3, %4, %5, %6, %7, %8, %9, %10, %11, %12, %13, %14, %15, "
      "%16, %17, %18, %19, %20, %21, %22, %23, %24, %25, %26, %27, %28, %29, %30, %31, "
      "%32, %33, %34, %35, %36, %37, %38, %39, %40, %41, %42, %43, %44, %45, %46, %47, "
      "%48, %49, %50, %51, %52, %53, %54, %55, %56, %57, %58, %59}, "
      "{%60, %61, %62, %63}, dsc, p, 1, 1, 1;\n}"
      : WG_ACC4(d, 0), WG_ACC4(d, 4), WG_ACC4(d, 8), WG_ACC4(d, 12), WG_ACC4(d, 16), WG_ACC4(d, 20), WG_ACC4(d, 24), WG_ACC4(d, 28), WG_ACC4(d, 32), WG_ACC4(d, 36), WG_ACC4(d, 40), WG_ACC4(d, 44), WG_ACC4(d, 48), WG_ACC4(d, 52), WG_ACC4(d, 56)
      : "r"(a0), "r"(a1), "r"(a2), "r"(a3), "r"(lo), "r"(hi));
}
__device__ __forceinline__ void wgmma_n120_init(float (&d)[60], uint32_t a0, uint32_t a1, uint32_t a2, uint32_t a3, uint32_t lo, uint32_t hi) {
  asm volatile(
      "{\n.reg .b64 dsc;\n.reg .pred p;\n"
      "mov.b64 dsc, {%64, %65};\nsetp.ne.b32 p, 0, 0;\n"
      "wgmma.mma_async.sync.aligned.m64n120k16.f32.bf16.bf16 "
      "{%0, %1, %2, %3, %4, %5, %6, %7, %8, %9, %10, %11, %12, %13, %14, %15, "
      "%16, %17, %18, %19, %20, %21, %22, %23, %24, %25, %26, %27, %28, %29, %30, %31, "
      "%32, %33, %34, %35, %36, %37, %38, %39, %40, %41, %42, %43, %44, %45, %46, %47, "
      "%48, %49, %50, %51, %52, %53, %54, %55, %56, %57, %58, %59}, "
      "{%60, %61, %62, %63}, dsc, p, 1, 1, 1;\n}"
      : WG_OUT4(d, 0), WG_OUT4(d, 4), WG_OUT4(d, 8), WG_OUT4(d, 12), WG_OUT4(d, 16), WG_OUT4(d, 20), WG_OUT4(d, 24), WG_OUT4(d, 28), WG_OUT4(d, 32), WG_OUT4(d, 36), WG_OUT4(d, 40), WG_OUT4(d, 44), WG_OUT4(d, 48), WG_OUT4(d, 52), WG_OUT4(d, 56)
      : "r"(a0), "r"(a1), "r"(a2), "r"(a3), "r"(lo), "r"(hi));
}
__device__ __forceinline__ void wgmma_n128(float (&d)[64], uint32_t a0, uint32_t a1, uint32_t a2, uint32_t a3, uint32_t lo, uint32_t hi) {
  asm volatile(
      "{\n.reg .b64 dsc;\n.reg .pred p;\n"
      "mov.b64 dsc, {%68, %69};\nsetp.ne.b32 p, 1, 0;\n"
      "wgmma.mma_async.sync.aligned.m64n128k16.f32.bf16.bf16 "
      "{%0, %1, %2, %3, %4, %5, %6, %7, %8, %9, %10, %11, %12, %13, %14, %15, "
      "%16, %17, %18, %19, %20, %21, %22, %23, %24, %25, %26, %27, %28, %29, %30, %31, "
      "%32, %33, %34, %35, %36, %37, %38, %39, %40, %41, %42, %43, %44, %45, %46, %47, "
      "%48, %49, %50, %51, %52, %53, %54, %55, %56, %57, %58, %59, %60, %61, %62, %63}, "
      "{%64, %65, %66, %67}, dsc, p, 1, 1, 1;\n}"
      : WG_ACC4(d, 0), WG_ACC4(d, 4), WG_ACC4(d, 8), WG_ACC4(d, 12), WG_ACC4(d, 16), WG_ACC4(d, 20), WG_ACC4(d, 24), WG_ACC4(d, 28), WG_ACC4(d, 32), WG_ACC4(d, 36), WG_ACC4(d, 40), WG_ACC4(d, 44), WG_ACC4(d, 48), WG_ACC4(d, 52), WG_ACC4(d, 56), WG_ACC4(d, 60)
      : "r"(a0), "r"(a1), "r"(a2), "r"(a3), "r"(lo), "r"(hi));
}
__device__ __forceinline__ void wgmma_n128_init(float (&d)[64], uint32_t a0, uint32_t a1, uint32_t a2, uint32_t a3, uint32_t lo, uint32_t hi) {
  asm volatile(
      "{\n.reg .b64 dsc;\n.reg .pred p;\n"
      "mov.b64 dsc, {%68, %69};\nsetp.ne.b32 p, 0, 0;\n"
      "wgmma.mma_async.sync.aligned.m64n128k16.f32.bf16.bf16 "
      "{%0, %1, %2, %3, %4, %5, %6, %7, %8, %9, %10, %11, %12, %13, %14, %15, "
      "%16, %17, %18, %19, %20, %21, %22, %23, %24, %25, %26, %27, %28, %29, %30, %31, "
      "%32, %33, %34, %35, %36, %37, %38, %39, %40, %41, %42, %43, %44, %45, %46, %47, "
      "%48, %49, %50, %51, %52, %53, %54, %55, %56, %57, %58, %59, %60, %61, %62, %63}, "
      "{%64, %65, %66, %67}, dsc, p, 1, 1, 1;\n}"
      : WG_OUT4(d, 0), WG_OUT4(d, 4), WG_OUT4(d, 8), WG_OUT4(d, 12), WG_OUT4(d, 16), WG_OUT4(d, 20), WG_OUT4(d, 24), WG_OUT4(d, 28), WG_OUT4(d, 32), WG_OUT4(d, 36), WG_OUT4(d, 40), WG_OUT4(d, 44), WG_OUT4(d, 48), WG_OUT4(d, 52), WG_OUT4(d, 56), WG_OUT4(d, 60)
      : "r"(a0), "r"(a1), "r"(a2), "r"(a3), "r"(lo), "r"(hi));
}

__device__ __forceinline__ void center_rows(uint32_t (&A)[112], uint32_t& m0, uint32_t& m1, float& dm0, float& dm1) {
  float c[14][4];
#pragma unroll
  for (int i = 0; i < 14; i++) c[i][0] = c[i][1] = c[i][2] = c[i][3] = 0.f;
#pragma unroll
  for (int s = 0; s < 28; s++) mma16816(c[s % 14], A[4 * s], A[4 * s + 1], A[4 * s + 2], A[4 * s + 3], 0x3f803f80u, 0x3f803f80u);
  float mu0 = 0.f, mu1 = 0.f;
  {
    float t0[7], t1[7];
#pragma unroll
    for (int i = 0; i < 7; i++) { t0[i] = c[i][0] + c[i + 7][0]; t1[i] = c[i][2] + c[i + 7][2]; }
    mu0 = (((t0[0] + t0[1]) + (t0[2] + t0[3])) + ((t0[4] + t0[5]) + t0[6])) * (1.f / DM);
    mu1 = (((t1[0] + t1[1]) + (t1[2] + t1[3])) + ((t1[4] + t1[5]) + t1[6])) * (1.f / DM);
  }
  m0 = pack_bf16(mu0, mu0);
  m1 = pack_bf16(mu1, mu1);
  dm0 = mu0 - bf_lo(m0);
  dm1 = mu1 - bf_lo(m1);
#pragma unroll
  for (int s = 0; s < 28; s++) {
    A[4 * s] = bf2_sub(A[4 * s], m0);
    A[4 * s + 1] = bf2_sub(A[4 * s + 1], m1);
    A[4 * s + 2] = bf2_sub(A[4 * s + 2], m0);
    A[4 * s + 3] = bf2_sub(A[4 * s + 3], m1);
  }
}
template <int S0, int NS>
__device__ __forceinline__ void sumsq_part(const uint32_t (&A)[112], float (&q)[2]) {
#pragma unroll
  for (int s = S0; s < S0 + NS; s++) {
#pragma unroll
    for (int e = 0; e < 4; e++)
      asm volatile(
          "{\n.reg .b32 lo, hi;\nshl.b32 lo, %1, 16;\nand.b32 hi, %1, 0xffff0000;\n"
          "fma.rn.f32 %0, lo, lo, %0;\nfma.rn.f32 %0, hi, hi, %0;\n}"
          : "+f"(q[e & 1])
          : "r"(A[4 * s + e]));
  }
}
__device__ __forceinline__ float rstd_of(float sumsq, float dm) {
  return rsqrtf(fmaxf(sumsq * (1.f / DM) - dm * dm, 0.f) + 1e-5f);
}
__device__ __forceinline__ void finish_rstd(const float (&q)[2], float dm0, float dm1, float& rs0, float& rs1) {
  float s0 = q[0], s1 = q[1];
  s0 += __shfl_xor_sync(~0u, s0, 1);
  s1 += __shfl_xor_sync(~0u, s1, 1);
  s0 += __shfl_xor_sync(~0u, s0, 2);
  s1 += __shfl_xor_sync(~0u, s1, 2);
  rs0 = rstd_of(s0, dm0);
  rs1 = rstd_of(s1, dm1);
}

__device__ __forceinline__ constexpr int xword(int sl, int i) {
  return 4 * (7 * (sl >> 1) + ((sl & 1) ? 4 : 0) + i);
}
__device__ __forceinline__ constexpr int xsingle(int sl) { return 4 * (7 * (sl >> 1) + 3) + 2 * (sl & 1); }
template <int T, int STRIDE>
__device__ __forceinline__ void load_xtile(uint32_t (&A)[112], const char* base, int lane) {
#pragma unroll
  for (int sl = 2 * T; sl < 2 * T + 2; sl++) {
    const char* p = base + sl * STRIDE;
#pragma unroll
    for (int i = 0; i < 3; i++) {
      uint4 v = ldx16(p + i * 512 + lane * 16);
      A[xword(sl, i)] = v.x; A[xword(sl, i) + 1] = v.y; A[xword(sl, i) + 2] = v.z; A[xword(sl, i) + 3] = v.w;
    }
    uint2 v3 = ldx8(p + 1536 + lane * 8);
    A[xsingle(sl)] = v3.x; A[xsingle(sl) + 1] = v3.y;
  }
}
template <int T, int STRIDE>
__device__ __forceinline__ void check_xtile(uint32_t (&A)[112], const char* base, int lane) {
  uint32_t it = 0;
#pragma unroll 1
  while (true) {
    uint32_t m = min(min(A[xword(2 * T, 0)], A[xword(2 * T, 1)]), min(A[xword(2 * T, 2)], A[xsingle(2 * T)]));
    m = min(m, min(min(A[xword(2 * T + 1, 0)], A[xword(2 * T + 1, 1)]), min(A[xword(2 * T + 1, 2)], A[xsingle(2 * T + 1)])));
    if (__all_sync(~0u, m != 0) || spin_expired(it)) break;
    load_xtile<T, STRIDE>(A, base, lane);
  }
}
__device__ __forceinline__ uint32_t* halo_hint(int rb, int p, int j) {
  return g_sync + ((rb * 2 + p) * 4 + 1 + (j >> 2)) * 64 + 25 + (j & 3);
}
__device__ __forceinline__ void wait_hint(const uint32_t* hint, uint32_t want) {
  uint32_t it = 0;
#pragma unroll 1
  while (true) {
    uint32_t v;
    asm volatile("ld.relaxed.gpu.global.u32 %0, [%1];" : "=r"(v) : "l"(hint) : "memory");
    if (__all_sync(~0u, v == want) || spin_expired(it)) break;
  }
}
__device__ __forceinline__ void post_hint(uint32_t* hint, uint32_t value, int lane) {
  __syncwarp();
  if (lane == 0) asm volatile("st.relaxed.gpu.global.u32 [%0], %1;" ::"l"(hint), "r"(value) : "memory");
}
__device__ __forceinline__ void store_slice(uint4* slice, const uint32_t (&w)[14], int lane) {
  char* p = reinterpret_cast<char*>(slice);
  stx16(p + lane * 16, nz(w[0]), w[1], w[2], w[3]);
  stx16(p + 512 + lane * 16, nz(w[4]), w[5], w[6], w[7]);
  stx16(p + 1024 + lane * 16, nz(w[8]), w[9], w[10], w[11]);
  stx8(p + 1536 + lane * 8, nz(w[12]), w[13]);
}
template <int KS>
__device__ __forceinline__ constexpr uint32_t xoff() {
  return KS < 4 ? 2048u * KS : 7168u + 2048u * (KS - 4);
}

__device__ __forceinline__ uint2 load_h_block(const char* htile, int b, int lane) {
  int sl = b / 7, i = b - sl * 7;
  const char* p = htile + sl * 1920 + (i < 6 ? (i >> 1) * 512 + lane * 16 + (i & 1) * 8 : 1536 + lane * 8);
  return ldx8(p);
}

struct Params {
  CUtensorMap tx, tqkv, two, tw1, tw1n, tw2;
  const void *wqkv, *wo, *w1, *w2;
};

template <int IDX>
__device__ __forceinline__ void wait_stage(uint32_t bars) {
  mbar_wait(bars + full_bar(IDX) * 8, full_par(IDX));
  TS2(IDX);
}
__device__ __forceinline__ void release_stage(uint32_t bars, int slot, uint32_t cnt, int lane) {
  __syncwarp();
  if (lane == 0) {
    mbar_arrive_cluster(bars + (NST + slot) * 8, 0, cnt);
    mbar_arrive_cluster(bars + (NST + slot) * 8, 1, cnt);
  }
}

template <int IDX>
__device__ __forceinline__ void issue_weight_tile(const Params& prm, int t, int j, uint32_t dst, uint32_t bar) {
  const CUtensorMap* tm;
  int c0, c1;
  if constexpr (IDX < 8) {
    tm = &prm.tqkv; c0 = DM * (1 + t) + 56 * j; c1 = 112 * (IDX - 4);
  } else if constexpr (IDX < 10) {
    tm = &prm.tqkv; c0 = 56 * j; c1 = 112 * (2 * (IDX - 8) + t);
  } else if constexpr (IDX < 12) {
    tm = &prm.two; c0 = 56 * j; c1 = 112 * (2 * (IDX - 10) + t);
  } else if constexpr (IDX < 20) {
    tm = (IDX >= 16 && t == 1) ? &prm.tw1n : &prm.tw1;
    c0 = 224 * j + 128 * ((IDX - 12) >> 2) + 64 * t; c1 = 112 * ((IDX - 12) & 3);
  } else if constexpr (IDX < 26) {
    tm = &prm.tw2; c0 = 128 * ((IDX - 20) >> 1) + 64 * t; c1 = 224 * j + 112 * ((IDX - 20) & 1);
  } else {
    tm = &prm.tw2; c0 = 384; c1 = 224 * j + 112 * t;
  }
  tma_load_mc<2>(dst, tm, bar, c0, c1, 0);
}
template <int IDX>
__device__ __forceinline__ void produce_stage(const Params& prm, uint32_t sbase, uint32_t bars, int rb, int j, int crank) {
  constexpr int slot = slot_of(IDX);
  const uint32_t full = bars + full_bar(IDX) * 8;
  constexpr int prev = (slot == 1 && IDX >= 18) ? use_of(IDX) - 2 : use_of(IDX) - 1;
  if constexpr (prev >= 0) mbar_wait(bars + (NST + slot) * 8, prev & 1);
  if constexpr (IDX == 18) mbar_wait(bars + 25 * 8, 0);
  if constexpr (IDX == GATE_A_STAGE) mbar_wait(bars + GATE_A_BAR * 8, 0);
  if constexpr (IDX == GATE_B_STAGE) mbar_wait(bars + GATE_B_BAR * 8, 0);
  const uint32_t dst = sbase + slot * STAGE_B;
  TS2(IDX);
  mbar_expect_tx(full, stage_bytes(IDX));
  if constexpr (IDX < 4) {
    constexpr int p = IDX >> 1, w0 = (IDX & 1) * 2;
    tma_load<4>(dst, &prm.tx, full, 0, 64 * rb + 16 * w0, 0, p);
    tma_load<4>(dst + TILE_B, &prm.tx, full, 0, 64 * rb + 16 * (w0 + 1), 0, p);
  } else {
    issue_weight_tile<IDX>(prm, crank, j, dst + crank * TILE_B, full);
  }
}
template <int IDX>
__device__ __forceinline__ void produce_from(const Params& prm, uint32_t sbase, uint32_t bars, int rb, int j, int crank) {
  if constexpr (IDX < NSTAGE_TOTAL) {
    produce_stage<IDX>(prm, sbase, bars, rb, j, crank);
    produce_from<IDX + 1>(prm, sbase, bars, rb, j, crank);
  }
}
__device__ __forceinline__ bool elect_one() {
  uint32_t pred;
  asm volatile("{\n.reg .pred p;\nelect.sync _|p, 0xffffffff;\nselp.u32 %0, 1, 0, p;\n}" : "=r"(pred));
  return pred != 0;
}

__global__ void __launch_bounds__(NTHREADS, 1)
fused_block_kernel(const __grid_constant__ Params prm, const __nv_bfloat16* __restrict__ x, __nv_bfloat16* __restrict__ out) {
  extern __shared__ __align__(1024) uint8_t smem[];
  const uint32_t sbase = smem_u32(smem);
  const uint32_t bars = sbase + BAR_OFF;
  const int warp = __shfl_sync(~0u, (int)(threadIdx.x >> 5), 0), lane = threadIdx.x & 31;
  const int crank = blockIdx.x & 1;
  const int cl = blockIdx.x >> 1;
  const int set = cl < 4 ? 15 : (cl < 36 ? ((cl - 4) & 7) : 8 + (cl - 36) % 7);
  const int pos = cl < 4 ? cl : (cl < 36 ? ((cl - 4) >> 3) : (cl - 36) / 7);
  const int j = 4 * (set >> 3) + pos;
  const int rb = 2 * (set & 7) + crank;

  if (threadIdx.x == 0) {
#pragma unroll
    for (int i = 0; i < NST; i++) {
      mbar_init(bars + i * 8, 1);
      mbar_init(bars + (NST + i) * 8, USE_MC ? 16 : 8);
    }
    mbar_init(bars + 16 * 8, 1);
    for (int i = 18; i < 22; i++) mbar_init(bars + i * 8, 4);
    mbar_init(bars + 22 * 8, 1);
    mbar_init(bars + 23 * 8, 1);
    mbar_init(bars + 24 * 8, 2);
    mbar_init(bars + 25 * 8, USE_MC ? 16 : 8);
    asm volatile("fence.mbarrier_init.release.cluster;" ::: "memory");
  }
  __syncthreads();
  asm volatile("barrier.cluster.arrive.relaxed.aligned;\nbarrier.cluster.wait.aligned;" ::: "memory");
  TS(0);

  if (warp >= 8) {
    asm volatile("setmaxnreg.dec.sync.aligned.u32 24;");
    if (warp == 8) {
      if (elect_one()) {
        produce_stage<0>(prm, sbase, bars, rb, j, crank);
        produce_stage<1>(prm, sbase, bars, rb, j, crank);
        produce_stage<4>(prm, sbase, bars, rb, j, crank);
        produce_stage<5>(prm, sbase, bars, rb, j, crank);
        produce_stage<6>(prm, sbase, bars, rb, j, crank);
        produce_stage<7>(prm, sbase, bars, rb, j, crank);
        produce_stage<8>(prm, sbase, bars, rb, j, crank);
        produce_stage<9>(prm, sbase, bars, rb, j, crank);
        produce_stage<2>(prm, sbase, bars, rb, j, crank);
        produce_stage<3>(prm, sbase, bars, rb, j, crank);
        produce_from<10>(prm, sbase, bars, rb, j, crank);
      }
    } else if (warp == 11 && PF_START) {
      if (lane == 0) {
        const char* xs = reinterpret_cast<const char*>(x) + (size_t)(rb * 8 + j) * 14336;
        const char* ws = reinterpret_cast<const char*>(prm.wqkv) + (size_t)(rb * 8 + j) * 9408;
        asm volatile("cp.async.bulk.prefetch.L2.global [%0], %1;" ::"l"(xs), "r"(14336) : "memory");
        asm volatile("cp.async.bulk.prefetch.L2.global [%0], %1;" ::"l"(ws), "r"(9408) : "memory");
        if (PF_START > 1) {
          const char* wo = reinterpret_cast<const char*>(prm.wo) + (size_t)(rb * 8 + j) * 3136;
          asm volatile("cp.async.bulk.prefetch.L2.global [%0], %1;" ::"l"(wo), "r"(3136) : "memory");
        }
        if (PF_START > 2) {
          const char* w1 = reinterpret_cast<const char*>(prm.w1) + (size_t)(rb * 8 + j) * 12544;
          const char* w2 = reinterpret_cast<const char*>(prm.w2) + (size_t)(rb * 8 + j) * 12544;
          asm volatile("cp.async.bulk.prefetch.L2.global [%0], %1;" ::"l"(w1), "r"(12544) : "memory");
          asm volatile("cp.async.bulk.prefetch.L2.global [%0], %1;" ::"l"(w2), "r"(12544) : "memory");
        }
      }
    } else if (warp == 9 && !NO_PREFETCH) {
      mbar_wait(bars + full_bar(PF_STAGE) * 8, full_par(PF_STAGE));
      const int b = blockIdx.x;
      const char* wq = reinterpret_cast<const char*>(prm.wqkv);
      for (int u = b * 25 + lane; u < b * 25 + 25 && u < 3136; u += 32)
        asm volatile("prefetch.global.L2 [%0];" ::"l"(wq + (u / 7) * 2688 + (u % 7) * 128));
      const char* wo = reinterpret_cast<const char*>(prm.wo);
      for (int u = b * 25 + lane; u < b * 25 + 25 && u < 3136; u += 32)
        asm volatile("prefetch.global.L2 [%0];" ::"l"(wo + u * 128));
      const char* w1 = reinterpret_cast<const char*>(prm.w1);
      const char* w2 = reinterpret_cast<const char*>(prm.w2);
#pragma unroll
      for (int i = 0; i < 4; i++) {
        const int u = b * 98 + i * 32 + lane;
        if (i * 32 + lane < 98) asm volatile("prefetch.global.L2 [%0];" ::"l"(w1 + u * 128));
      }
#pragma unroll
      for (int i = 0; i < 4; i++) {
        const int u = b * 98 + i * 32 + lane;
        if (i * 32 + lane < 98) asm volatile("prefetch.global.L2 [%0];" ::"l"(w2 + u * 128));
      }
    } else if (warp == 10) {
      const uint32_t zsrc = sbase + ZERO_OFF;
      for (int i = lane * 16; i < ZERO_B; i += 512) asm volatile("st.shared.v4.b32 [%0], {%1,%1,%1,%1};" ::"r"(zsrc + i), "r"(0) : "memory");
      asm volatile("fence.proxy.async.shared::cta;" ::: "memory");
      __syncwarp();
      mbar_wait(bars + 16 * 8, 0);
      mbar_wait(bars + full_bar(CLEAR_STAGE) * 8, full_par(CLEAR_STAGE));
      if (lane == 0) {
        uint32_t np;
        asm volatile("ld.shared.u32 %0, [%1];" : "=r"(np) : "r"(bars + 17 * 8) : "memory");
        np = (np & 1) ^ 1;
        for (int t = 0; t < 8; t++) bulk_store(g_O[np] + ((rb * 8 + t) * 8 + j) * 112, zsrc, 1792);
        for (int p = 0; p < 2; p++) bulk_store(g_halo[np] + ((rb * 2 + p) * 8 + j) * 128, zsrc, 2048);
        for (int t = 0; t < 8; t++) bulk_store(g_H[np] + ((rb * 8 + t) * 8 + j) * 120, zsrc, 1920);
        asm volatile("cp.async.bulk.commit_group;\ncp.async.bulk.wait_group 0;" ::: "memory");
      }
    }
  } else {
    asm volatile("setmaxnreg.inc.sync.aligned.u32 240;");
    const int p = warp >> 2, w = warp & 3;
    const int r = lane >> 2, q = lane & 3;
    const int tile_id = (rb * 2 + p) * 4 + w;
    const int tok0 = 128 * rb + 32 * w + p + 2 * r;
    const uint32_t dbase0 = ((sbase & 0x3ffffu) >> 4) | DESC_LBO;

    constexpr uint32_t dhi = DESC_HI, dhi_far = DESC_HI_FAR;

    uint32_t* sync = g_sync + tile_id * 64;
    uint32_t epoch, epoch2;
    asm volatile("ld.relaxed.gpu.global.u32 %0, [%1];" : "=r"(epoch) : "l"(sync + lane) : "memory");
    asm volatile("ld.relaxed.gpu.global.u32 %0, [%1];" : "=r"(epoch2) : "l"(sync + 32 + lane) : "memory");

    uint32_t A[112];
    {
      const int xslot = w >> 1;
      mbar_wait(bars + (p == 0 ? xslot : 22 + xslot) * 8, 0);
      TS(1);
      const uint32_t tb = sbase + xslot * STAGE_B + (w & 1) * TILE_B;
      const int row = (lane & 7) + ((lane >> 3) & 1) * 8;
      const uint32_t rowa = tb + row * 128;
#pragma unroll
      for (int s = 0; s < 28; s++) {
        const uint32_t unit = 2 * (s & 3) + (lane >> 4);
        const uint32_t addr = rowa + (s >> 2) * 2048 + ((unit ^ (row & 7)) << 4);
        asm volatile("ldmatrix.sync.aligned.m8n8.x4.shared.b16 {%0,%1,%2,%3}, [%4];"
                     : "=r"(A[4 * s]), "=r"(A[4 * s + 1]), "=r"(A[4 * s + 2]), "=r"(A[4 * s + 3])
                     : "r"(addr)
                     : "memory");
      }
      release_stage(bars, xslot, 4, lane);
      if (p == 1 && w >= 2 && lane == 0) mbar_arrive(bars + 24 * 8, 1);
    }
    epoch = __shfl_sync(~0u, epoch, SY_EPOCH);
    epoch2 = __shfl_sync(~0u, epoch2, SY_EPOCH2 - 32);
    const uint32_t stamp = epoch + 1;
    const int par = epoch & 1;
    const uint32_t tag = (epoch2 & 1) ^ 1;
    if (warp == 0 && lane == 0) {
      asm volatile("st.shared.u32 [%0], %1;" ::"r"(bars + 17 * 8), "r"(epoch) : "memory");
      mbar_arrive(bars + 16 * 8, 1);
    }
    float dm0, dm1;
    uint32_t m0, m1;
    center_rows(A, m0, m1, dm0, dm1);
    TS(2);

    if (p == 1) asm volatile("bar.sync 1, 256;" ::: "memory");
    float akv[60], aq[28];
    float sq[2] = {0.f, 0.f};
#define KV_STAGE(Q)                                                                                         \
    {                                                                                                       \
      wait_stage<4 + Q>(bars);                                                                              \
      const uint32_t dbase = opaque(dbase0);                                                                \
      wg_fence();                                                                                           \
      _Pragma("unroll") for (int ks = 0; ks < 7; ks++) {                                                    \
        const int s = 7 * Q + ks;                                                                           \
        const uint32_t d = dbase + ((slot_of(4 + Q) * STAGE_B + ks * 2048) >> 4);                          \
        if (Q == 0 && ks == 0) wgmma_n120_init(akv, A[4 * s], A[4 * s + 1], A[4 * s + 2], A[4 * s + 3], d, dhi); \
        else wgmma_n120(akv, A[4 * s], A[4 * s + 1], A[4 * s + 2], A[4 * s + 3], d, dhi);                   \
      }                                                                                                     \
      wg_commit();                                                                                          \
      sumsq_part<7 * Q, 7>(A, sq);                                                                            \
      if (Q > 0) { wg_wait<1>(); release_stage(bars, slot_of(4 + Q - 1), 1, lane); }                         \
    }
    KV_STAGE(0) KV_STAGE(1) KV_STAGE(2) KV_STAGE(3)
#define Q_STAGE(T)                                                                                          \
    {                                                                                                       \
      wait_stage<8 + T>(bars);                                                                              \
      const uint32_t dbase = opaque(dbase0);                                                                \
      wg_fence();                                                                                           \
      _Pragma("unroll") for (int u = 0; u < 14; u++) {                                                      \
        const int s = 14 * T + u;                                                                           \
        const uint32_t d = dbase + ((slot_of(8 + T) * STAGE_B + (u / 7) * TILE_B + (u % 7) * 2048) >> 4);  \
        if (T == 0 && u == 0) wgmma_n56_init(aq, A[4 * s], A[4 * s + 1], A[4 * s + 2], A[4 * s + 3], d, dhi); \
        else wgmma_n56(aq, A[4 * s], A[4 * s + 1], A[4 * s + 2], A[4 * s + 3], d, dhi);                 \
      }                                                                                                     \
      wg_commit();                                                                                          \
    }
    Q_STAGE(0) Q_STAGE(1)
    if (p == 0) asm volatile("bar.arrive 1, 256;" ::: "memory");
    float rs0, rs1;
    finish_rstd(sq, dm0, dm1, rs0, rs1);
    wg_wait<2>();
    reg_fence(akv);
    release_stage(bars, slot_of(7), 1, lane);
    TS(3);

    uint32_t kb[14], vb[14], kp[7], vp[7];
#pragma unroll
    for (int b = 0; b < 7; b++) {
      kb[2 * b] = pack_bf16(akv[4 * b] * rs0, akv[4 * b + 1] * rs0);
      kb[2 * b + 1] = pack_bf16(akv[4 * b + 2] * rs1, akv[4 * b + 3] * rs1);
      vb[2 * b] = pack_bf16(akv[32 + 4 * b] * rs0, akv[32 + 4 * b + 1] * rs0);
      vb[2 * b + 1] = pack_bf16(akv[32 + 4 * b + 2] * rs1, akv[32 + 4 * b + 3] * rs1);
    }
    mbar_wait(bars + 24 * 8, 0);
    if (w < 3) {
      const uint32_t hb = sbase + HAND_OFF + (p * 3 + w) * 2048 + lane * 16;
      asm volatile("st.shared.v4.b32 [%0], {%1,%2,%3,%4};" ::"r"(hb), "r"(kb[1]), "r"(kb[3]), "r"(kb[5]), "r"(kb[7]) : "memory");
      asm volatile("st.shared.v4.b32 [%0], {%1,%2,%3,%4};" ::"r"(hb + 512), "r"(kb[9]), "r"(kb[11]), "r"(kb[13]), "r"(0) : "memory");
      asm volatile("st.shared.v4.b32 [%0], {%1,%2,%3,%4};" ::"r"(hb + 1024), "r"(vb[1]), "r"(vb[3]), "r"(vb[5]), "r"(vb[7]) : "memory");
      asm volatile("st.shared.v4.b32 [%0], {%1,%2,%3,%4};" ::"r"(hb + 1536), "r"(vb[9]), "r"(vb[11]), "r"(vb[13]), "r"(0) : "memory");
    } else if (rb < 15) {
      char* hp = reinterpret_cast<char*>(g_halo[par] + ((rb * 2 + p) * 8 + j) * 128) + lane * 16;
      stx16(hp, nz(kb[1]), kb[3], kb[5], kb[7]);
      stx16(hp + 512, nz(kb[9]), kb[11], kb[13], 0);
      stx16(hp + 1024, nz(vb[1]), vb[3], vb[5], vb[7]);
      stx16(hp + 1536, nz(vb[9]), vb[11], vb[13], 0);
      post_hint(halo_hint(rb + 1, p, j), stamp, lane);
    }
    asm volatile("bar.sync %0, 128;" ::"r"(2 + p) : "memory");
    if (w > 0) {
      const uint32_t hb = sbase + HAND_OFF + (p * 3 + w - 1) * 2048 + lane * 16;
      [[maybe_unused]] uint32_t z;
      asm volatile("ld.shared.v4.b32 {%0,%1,%2,%3}, [%4];" : "=r"(kp[0]), "=r"(kp[1]), "=r"(kp[2]), "=r"(kp[3]) : "r"(hb) : "memory");
      asm volatile("ld.shared.v4.b32 {%0,%1,%2,%3}, [%4];" : "=r"(kp[4]), "=r"(kp[5]), "=r"(kp[6]), "=r"(z) : "r"(hb + 512) : "memory");
      asm volatile("ld.shared.v4.b32 {%0,%1,%2,%3}, [%4];" : "=r"(vp[0]), "=r"(vp[1]), "=r"(vp[2]), "=r"(vp[3]) : "r"(hb + 1024) : "memory");
      asm volatile("ld.shared.v4.b32 {%0,%1,%2,%3}, [%4];" : "=r"(vp[4]), "=r"(vp[5]), "=r"(vp[6]), "=r"(z) : "r"(hb + 1536) : "memory");
    } else {
#pragma unroll
      for (int b = 0; b < 7; b++) kp[b] = vp[b] = 0;
    }
    release_stage(bars, 25 - NST, 1, lane);
#define HALO_WAIT wait_hint(halo_hint(rb, p, j), stamp);
#define HALO_READ                                                                                             \
    if (w == 0 && rb > 0) {                                                                                   \
      const char* hp = reinterpret_cast<const char*>(g_halo[par] + (((rb - 1) * 2 + p) * 8 + j) * 128) + lane * 16; \
      HALO_WAIT                                                                                               \
      uint4 u0, u1, u2, u3;                                                                                   \
      uint32_t t0 = 0;                                                                                        \
      _Pragma("unroll 1") while (true) {                                                                      \
        u0 = ldx16(hp); u1 = ldx16(hp + 512); u2 = ldx16(hp + 1024); u3 = ldx16(hp + 1536);                   \
        if (__all_sync(~0u, u0.x != 0 && u1.x != 0 && u2.x != 0 && u3.x != 0) || spin_expired(t0)) break;     \
      }                                                                                                       \
      kp[0] = u0.x; kp[1] = u0.y; kp[2] = u0.z; kp[3] = u0.w; kp[4] = u1.x; kp[5] = u1.y; kp[6] = u1.z;       \
      vp[0] = u2.x; vp[1] = u2.y; vp[2] = u2.z; vp[3] = u2.w; vp[4] = u3.x; vp[5] = u3.y; vp[6] = u3.z;       \
    }
    HALO_READ
    const bool has_prev = (w > 0) || (rb > 0);

    wg_wait<0>();
    reg_fence(aq);
    release_stage(bars, slot_of(8), 1, lane);
    release_stage(bars, slot_of(9), 1, lane);
    TS(4);

    uint32_t ob[14];
    {
      uint32_t qb[14];
#pragma unroll
      for (int b = 0; b < 7; b++) {
        qb[2 * b] = pack_bf16(aq[4 * b] * rs0, aq[4 * b + 1] * rs0);
        qb[2 * b + 1] = pack_bf16(aq[4 * b + 2] * rs1, aq[4 * b + 3] * rs1);
      }
      uint32_t vt[21];
#pragma unroll
      for (int b = 0; b < 7; b++) {
        vt[3 * b] = movmat(vp[b]);
        vt[3 * b + 1] = movmat(vb[2 * b]);
        vt[3 * b + 2] = movmat(vb[2 * b + 1]);
      }
      const float sc = 0.18898223650461362f * 1.4426950408889634f;
      const bool l0 = 2 * q > r, l1 = 2 * q + 1 > r;
      float sa[2][2][3][4];
#pragma unroll
      for (int h = 0; h < 2; h++) {
        const int b0 = h == 0 ? 0 : 3;
        const bool keep3 = h == 0 ? (q < 2) : (q >= 2);
#pragma unroll
        for (int ks = 0; ks < 2; ks++) {
          const int ba = b0 + 2 * ks, bb = ba + 1;
          uint32_t a0 = qb[2 * ba], a1 = qb[2 * ba + 1], a2 = qb[2 * bb], a3 = qb[2 * bb + 1];
          if (ba == 3 && h == 1) { a0 = keep3 ? a0 : 0u; a1 = keep3 ? a1 : 0u; }
          if (bb == 3 && h == 0) { a2 = keep3 ? a2 : 0u; a3 = keep3 ? a3 : 0u; }
#pragma unroll
          for (int t = 0; t < 3; t++) sa[h][ks][t][0] = sa[h][ks][t][1] = sa[h][ks][t][2] = sa[h][ks][t][3] = 0.f;
          mma16816(sa[h][ks][0], a0, a1, a2, a3, kp[ba], kp[bb]);
          mma16816(sa[h][ks][1], a0, a1, a2, a3, kb[2 * ba], kb[2 * bb]);
          mma16816(sa[h][ks][2], a0, a1, a2, a3, kb[2 * ba + 1], kb[2 * bb + 1]);
        }
      }
      uint32_t pa[2][4];
#pragma unroll
      for (int h = 0; h < 2; h++) {
        const float NEG = -INFINITY;
        float x00 = l0 ? sa[h][0][0][0] + sa[h][1][0][0] : sa[h][0][1][0] + sa[h][1][1][0];
        float x01 = l1 ? sa[h][0][0][1] + sa[h][1][0][1] : sa[h][0][1][1] + sa[h][1][1][1];
        float x10 = l0 ? sa[h][0][1][2] + sa[h][1][1][2] : sa[h][0][2][2] + sa[h][1][2][2];
        float x11 = l1 ? sa[h][0][1][3] + sa[h][1][1][3] : sa[h][0][2][3] + sa[h][1][2][3];
        x00 = (l0 && !has_prev) ? NEG : x00 * sc;
        x01 = (l1 && !has_prev) ? NEG : x01 * sc;
        x10 *= sc; x11 *= sc;
        float m0 = fmaxf(x00, x01), m1 = fmaxf(x10, x11);
        m0 = fmaxf(m0, __shfl_xor_sync(~0u, m0, 1));
        m1 = fmaxf(m1, __shfl_xor_sync(~0u, m1, 1));
        m0 = fmaxf(m0, __shfl_xor_sync(~0u, m0, 2));
        m1 = fmaxf(m1, __shfl_xor_sync(~0u, m1, 2));
        float p00 = ex2(x00 - m0), p01 = ex2(x01 - m0), p10 = ex2(x10 - m1), p11 = ex2(x11 - m1);
        float t0 = p00 + p01, t1 = p10 + p11;
        t0 += __shfl_xor_sync(~0u, t0, 1);
        t1 += __shfl_xor_sync(~0u, t1, 1);
        t0 += __shfl_xor_sync(~0u, t0, 2);
        t1 += __shfl_xor_sync(~0u, t1, 2);
        const float i0 = rcp(t0), i1 = rcp(t1);
        p00 *= i0; p01 *= i0; p10 *= i1; p11 *= i1;
        pa[h][0] = pack_bf16(l0 ? p00 : 0.f, l1 ? p01 : 0.f);
        pa[h][1] = pack_bf16(l0 ? 0.f : p00, l1 ? 0.f : p01);
        pa[h][2] = pack_bf16(l0 ? p10 : 0.f, l1 ? p11 : 0.f);
        pa[h][3] = pack_bf16(l0 ? 0.f : p10, l1 ? 0.f : p11);
      }
      float oacc[2][4][4], oex[2][4][4];
#pragma unroll
      for (int h = 0; h < 2; h++) {
#pragma unroll
        for (int u = 0; u < 4; u++) {
          const int b = (h == 0 ? 0 : 3) + u;
          oacc[h][u][0] = oacc[h][u][1] = oacc[h][u][2] = oacc[h][u][3] = 0.f;
          oex[h][u][0] = oex[h][u][1] = oex[h][u][2] = oex[h][u][3] = 0.f;
          mma16816(oacc[h][u], pa[h][0], 0u, pa[h][1], pa[h][2], vt[3 * b], vt[3 * b + 1]);
          mma1688(oex[h][u], 0u, pa[h][3], vt[3 * b + 2]);
        }
      }
#pragma unroll
      for (int h = 0; h < 2; h++)
#pragma unroll
        for (int u = 0; u < 4; u++) { oacc[h][u][2] += oex[h][u][2]; oacc[h][u][3] += oex[h][u][3]; }
#pragma unroll
      for (int b = 0; b < 7; b++) {
        float o0, o1, o2, o3;
        if (b < 3) { o0 = oacc[0][b][0]; o1 = oacc[0][b][1]; o2 = oacc[0][b][2]; o3 = oacc[0][b][3]; }
        else if (b > 3) { o0 = oacc[1][b - 3][0]; o1 = oacc[1][b - 3][1]; o2 = oacc[1][b - 3][2]; o3 = oacc[1][b - 3][3]; }
        else {
          const bool h0 = q < 2;
          o0 = h0 ? oacc[0][3][0] : oacc[1][0][0]; o1 = h0 ? oacc[0][3][1] : oacc[1][0][1];
          o2 = h0 ? oacc[0][3][2] : oacc[1][0][2]; o3 = h0 ? oacc[0][3][3] : oacc[1][0][3];
        }
        ob[2 * b] = pack_bf16(o0, o1);
        ob[2 * b + 1] = pack_bf16(o2, o3);
      }
    }
    PROBE(22);
    store_slice(g_O[par] + (tile_id * 8 + j) * 112, ob, lane);
    post_hint(sync + SY_O + j, stamp, lane);
    PROBE(24);
    TS(5);

    uint32_t xr[14];
    {
      const uint32_t* xp = reinterpret_cast<const uint32_t*>(x + (size_t)tok0 * DM + 56 * j + 2 * q);
#pragma unroll
      for (int b = 0; b < 7; b++) {
        xr[2 * b] = __ldg(xp + 4 * b);
        xr[2 * b + 1] = __ldg(xp + 4 * b + 16 * DM / 2);
      }
    }
    const char* otile = reinterpret_cast<const char*>(g_O[par] + tile_id * 8 * 112);
    wait_hint(sync + SY_O + (lane & 7), stamp);
    TS(16);
    load_xtile<0, 1792>(A, otile, lane);
    load_xtile<1, 1792>(A, otile, lane);
    load_xtile<2, 1792>(A, otile, lane);
    load_xtile<3, 1792>(A, otile, lane);
    XTS(20);
    float ah[28];
#define X_STEP(ACC, FN, T, KS, ADDR, FIRST)                                                                   \
    if (FIRST) FN##_init(ACC, A[28 * T + 4 * KS], A[28 * T + 4 * KS + 1], A[28 * T + 4 * KS + 2], A[28 * T + 4 * KS + 3], \
                         dbase + (((ADDR) + xoff<KS>()) >> 4), KS == 3 ? dhi_far : dhi);                      \
    else FN(ACC, A[28 * T + 4 * KS], A[28 * T + 4 * KS + 1], A[28 * T + 4 * KS + 2], A[28 * T + 4 * KS + 3],  \
            dbase + (((ADDR) + xoff<KS>()) >> 4), KS == 3 ? dhi_far : dhi);
#define X_TILE(ACC, FN, T, ADDR, FIRST)                                                                       \
    { const uint32_t dbase = opaque(dbase0); wg_fence();                                                      \
    X_STEP(ACC, FN, T, 0, ADDR, FIRST) X_STEP(ACC, FN, T, 1, ADDR, false) X_STEP(ACC, FN, T, 2, ADDR, false)   \
    X_STEP(ACC, FN, T, 3, ADDR, false) X_STEP(ACC, FN, T, 4, ADDR, false) X_STEP(ACC, FN, T, 5, ADDR, false)   \
    X_STEP(ACC, FN, T, 6, ADDR, false) }
    wait_stage<10>(bars);
    check_xtile<0, 1792>(A, otile, lane);
    XTS(21);
    X_TILE(ah, wgmma_n56, 0, slot_of(10) * STAGE_B, true)
    wg_commit();
    check_xtile<1, 1792>(A, otile, lane);
    XTS(22);
    X_TILE(ah, wgmma_n56, 1, slot_of(10) * STAGE_B + TILE_B, false)
    wg_commit();
    wait_stage<11>(bars);
    check_xtile<2, 1792>(A, otile, lane);
    XTS(23);
    X_TILE(ah, wgmma_n56, 2, slot_of(11) * STAGE_B, false)
    wg_commit();
    check_xtile<3, 1792>(A, otile, lane);
    if (lane == 0) mbar_arrive(bars + (18 + p) * 8, 1);
    TS(6);
    X_TILE(ah, wgmma_n56, 3, slot_of(11) * STAGE_B + TILE_B, false)
    wg_commit();
    wg_wait<2>();
    release_stage(bars, slot_of(10), 1, lane);
    wg_wait<0>();
    reg_fence(ah);
    release_stage(bars, slot_of(11), 1, lane);
    {
      uint32_t hb[14];
#pragma unroll
      for (int b = 0; b < 7; b++) {
        hb[2 * b] = bf2_add(xr[2 * b], pack_bf16(ah[4 * b], ah[4 * b + 1]));
        hb[2 * b + 1] = bf2_add(xr[2 * b + 1], pack_bf16(ah[4 * b + 2], ah[4 * b + 3]));
      }
      store_slice(g_H[par] + (tile_id * 8 + j) * 120, hb, lane);
      uint32_t d[14];
#pragma unroll
      for (int i = 0; i < 14; i++) d[i] = bf2_sub(hb[i], (i & 1) ? m1 : m0);
      float s0 = 0.f, s1 = 0.f, q0 = 0.f, q1 = 0.f;
#pragma unroll
      for (int b = 0; b < 7; b++) {
        const float a = bf_lo(d[2 * b]), c = bf_hi(d[2 * b]), e = bf_lo(d[2 * b + 1]), f = bf_hi(d[2 * b + 1]);
        s0 += a + c; q0 = fmaf(a, a, fmaf(c, c, q0));
        s1 += e + f; q1 = fmaf(e, e, fmaf(f, f, q1));
      }
#pragma unroll
      for (int o = 1; o < 4; o <<= 1) {
        s0 += __shfl_xor_sync(~0u, s0, o); q0 += __shfl_xor_sync(~0u, q0, o);
        s1 += __shfl_xor_sync(~0u, s1, o); q1 += __shfl_xor_sync(~0u, q1, o);
      }
      if (q < 2) {
        char* sp = reinterpret_cast<char*>(g_H[par] + (tile_id * 8 + j) * 120) + 1792 + (r + 8 * q) * 8;
        stx8(sp, __float_as_uint(q ? s1 : s0) | 1u, __float_as_uint(q ? q1 : q0));
      }
      post_hint(sync + SY_H + j, stamp, lane);
    }
    TS(7);

    const char* htile = reinterpret_cast<const char*>(g_H[par] + tile_id * 8 * 120);
    {
      wait_hint(sync + SY_H + (lane & 7), stamp);
      TS(19);
      const char* sp = htile + q * 3840 + 1792 + r * 8;
      uint2 ua = ldx8(sp), ub = ldx8(sp + 1920), uc = ldx8(sp + 64), ud = ldx8(sp + 1920 + 64);
      load_xtile<0, 1920>(A, htile, lane);
      load_xtile<1, 1920>(A, htile, lane);
      load_xtile<2, 1920>(A, htile, lane);
      load_xtile<3, 1920>(A, htile, lane);
      XTS(24);
      uint32_t it = 0;
#pragma unroll 1
      while (!__all_sync(~0u, min(min(ua.x, ub.x), min(uc.x, ud.x)) != 0) && !spin_expired(it)) {
        ua = ldx8(sp); ub = ldx8(sp + 1920); uc = ldx8(sp + 64); ud = ldx8(sp + 1920 + 64);
      }
      float s0 = __uint_as_float(ua.x) + __uint_as_float(ub.x), q0 = __uint_as_float(ua.y) + __uint_as_float(ub.y);
      float s1 = __uint_as_float(uc.x) + __uint_as_float(ud.x), q1 = __uint_as_float(uc.y) + __uint_as_float(ud.y);
#pragma unroll
      for (int o = 1; o < 4; o <<= 1) {
        s0 += __shfl_xor_sync(~0u, s0, o); q0 += __shfl_xor_sync(~0u, q0, o);
        s1 += __shfl_xor_sync(~0u, s1, o); q1 += __shfl_xor_sync(~0u, q1, o);
      }
      s0 *= 1.f / DM; s1 *= 1.f / DM;
      rs0 = rstd_of(q0, s0);
      rs1 = rstd_of(q1, s1);
      const float mu0 = bf_lo(m0) + s0, mu1 = bf_lo(m1) + s1;
      m0 = pack_bf16(mu0, mu0);
      m1 = pack_bf16(mu1, mu1);
    }
    uint32_t H1[56];
    {
      float a1[64];
#define CENTER_TILE(T)                                                                                        \
      check_xtile<T, 1920>(A, htile, lane);                                                                         \
      _Pragma("unroll") for (int i = 0; i < 28; i++) A[28 * T + i] = bf2_sub(A[28 * T + i], (i & 1) ? m1 : m0);
#define W1_STAGE(ACC, FN, IDX, T)                                                                             \
      wait_stage<IDX>(bars);                                                                                  \
      X_TILE(ACC, FN, T, slot_of(IDX) * STAGE_B, T == 0)                                                       \
      wg_commit();                                                                                            \
      if (T > 0) { wg_wait<1>(); release_stage(bars, slot_of(IDX - 1), 1, lane); }
      CENTER_TILE(0) XTS(25); W1_STAGE(a1, wgmma_n128, 12, 0)
      CENTER_TILE(1) XTS(26); W1_STAGE(a1, wgmma_n128, 13, 1)
      CENTER_TILE(2) XTS(27); W1_STAGE(a1, wgmma_n128, 14, 2)
      CENTER_TILE(3)
      if (lane == 0) mbar_arrive(bars + (20 + p) * 8, 1);
      TS(8);
      W1_STAGE(a1, wgmma_n128, 15, 3)
      wg_wait<0>();
      reg_fence(a1);
      release_stage(bars, slot_of(15), 1, lane);
#pragma unroll
      for (int b = 0; b < 16; b++) {
        H1[2 * b] = pack_bf16_relu(a1[4 * b] * rs0, a1[4 * b + 1] * rs0);
        H1[2 * b + 1] = pack_bf16_relu(a1[4 * b + 2] * rs1, a1[4 * b + 3] * rs1);
      }
    }
    TS(9);
    {
      float a2[48];
      W1_STAGE(a2, wgmma_n96, 16, 0)
      W1_STAGE(a2, wgmma_n96, 17, 1)
      W1_STAGE(a2, wgmma_n96, 18, 2)
      W1_STAGE(a2, wgmma_n96, 19, 3)
      wg_wait<0>();
      reg_fence(a2);
      release_stage(bars, slot_of(19), 1, lane);
#pragma unroll
      for (int b = 0; b < 12; b++) {
        H1[32 + 2 * b] = pack_bf16_relu(a2[4 * b] * rs0, a2[4 * b + 1] * rs0);
        H1[32 + 2 * b + 1] = pack_bf16_relu(a2[4 * b + 2] * rs1, a2[4 * b + 3] * rs1);
      }
    }
    TS(10);

    __nv_bfloat16* orow = out + (size_t)tok0 * DM;
    const uint32_t eye = (r == 2 * q ? 0x00003f80u : 0u) | (r == 2 * q + 1 ? 0x3f800000u : 0u);

#define W2_HALF(ACC, IDX, KH)                                                                                 \
    wait_stage<IDX>(bars);                                                                                    \
    wg_fence();                                                                                               \
    _Pragma("unroll") for (int ks = 0; ks < 7; ks++) {                                                        \
      const int s = 7 * KH + ks;                                                                              \
      const uint32_t d = opaque(dbase0) + ((slot_of(IDX) * STAGE_B + ks * 2048) >> 4);                                  \
      if (KH == 0 && ks == 0) wgmma_n128_init(ACC, H1[4 * s], H1[4 * s + 1], H1[4 * s + 2], H1[4 * s + 3], d, dhi); \
      else wgmma_n128(ACC, H1[4 * s], H1[4 * s + 1], H1[4 * s + 2], H1[4 * s + 3], d, dhi);               \
    }                                                                                                         \
    wg_commit();
#define P_STORE(ACC, C)                                                                                       \
    {                                                                                                         \
      uint4* pp = g_P + (tile_id * 8 + j) * 896 + C * 256 + lane;                                             \
      _Pragma("unroll") for (int o = 0; o < 8; o++)                                                           \
        stx16(pp + o * 32, (pack_bf16(ACC[8 * o], ACC[8 * o + 1]) & ~1u) | tag, pack_bf16(ACC[8 * o + 2], ACC[8 * o + 3]), \
              pack_bf16(ACC[8 * o + 4], ACC[8 * o + 5]), pack_bf16(ACC[8 * o + 6], ACC[8 * o + 7]));          \
    }
    const uint4* pp = g_P + tile_id * 8 * 896 + j * 32 + lane;
    const uint2* p3 = reinterpret_cast<const uint2*>(g_P + tile_id * 8 * 896 + 768) + j * 32 + lane;
    uint4 v0[8], v1[8];
    uint2 hr[8];
    {
      float b0[64], b1[64];
      W2_HALF(b0, 20, 0)
      W2_HALF(b0, 21, 1)
      W2_HALF(b1, 22, 0)
      wg_wait<1>();
      reg_fence(b0);
      W2_HALF(b1, 23, 1)
      P_STORE(b0, 0)
      post_hint(sync + SY_P0 + j, stamp, lane);
      W2_HALF(b0, 24, 0)
      wg_wait<1>();
      reg_fence(b1);
      W2_HALF(b0, 25, 1)
      P_STORE(b1, 1)
      post_hint(sync + SY_P1 + j, stamp, lane);
      TS(11);
      float b3[32];
      wait_stage<26>(bars);
      wg_fence();
#pragma unroll
      for (int s = 0; s < 14; s++) {
        const uint32_t d = opaque(dbase0) + ((slot_of(26) * STAGE_B + (s / 7) * TILE_B + (s % 7) * 2048) >> 4);
        if (s == 0) wgmma_n64_init(b3, H1[4 * s], H1[4 * s + 1], H1[4 * s + 2], H1[4 * s + 3], d, dhi);
        else wgmma_n64(b3, H1[4 * s], H1[4 * s + 1], H1[4 * s + 2], H1[4 * s + 3], d, dhi);
      }
      wg_commit();
      TTS(20);
      wait_hint(sync + SY_P0 + (lane & 7), stamp);
      TTS(21);
#pragma unroll
      for (int s = 0; s < 8; s++) v0[s] = ldx16(pp + s * 896);
#pragma unroll
      for (int c = 0; c < 3; c++) {
        hr[2 * c] = load_h_block(htile, 16 * c + 2 * j, lane);
        hr[2 * c + 1] = load_h_block(htile, 16 * c + 2 * j + 1, lane);
      }
      hr[6] = load_h_block(htile, 48 + 2 * (j >> 1), lane);
      hr[7] = load_h_block(htile, 48 + 2 * (j >> 1) + 1, lane);
      wg_wait<1>();
      reg_fence(b0);
      P_STORE(b0, 2)
      post_hint(sync + SY_P2 + j, stamp, lane);
      wg_wait<0>();
      reg_fence(b3);
      TS(12);
      uint2* ps = reinterpret_cast<uint2*>(g_P + (tile_id * 8 + j) * 896 + 768) + lane;
#pragma unroll
      for (int o = 0; o < 8; o++) {
        const int ba = 2 * (o >> 1), hf = o & 1;
        stx8(ps + o * 32, (pack_bf16(b3[4 * ba + 2 * hf], b3[4 * ba + 2 * hf + 1]) & ~1u) | tag,
             pack_bf16(b3[4 * (ba + 1) + 2 * hf], b3[4 * (ba + 1) + 2 * hf + 1]));
      }
      post_hint(sync + SY_P3 + j, stamp, lane);
      TTS(22);
    }
    {
      const int hf = j & 1;
      const bool odd = q & 1;
      const int coff = odd ? 8 + 2 * (q - 1) : 2 * q;
#define P_CHECK(V, OFF)                                                                                       \
      {                                                                                                       \
        uint32_t it = 0;                                                                                      \
        _Pragma("unroll 1") while (true) {                                                                    \
          uint32_t bad = 0;                                                                                   \
          _Pragma("unroll") for (int s = 0; s < 8; s++) bad |= V[s].x ^ tag;                                  \
          if (__all_sync(~0u, (bad & 1) == 0) || spin_expired(it)) break;                                     \
          _Pragma("unroll") for (int s = 0; s < 8; s++) V[s] = ldx16(pp + OFF + s * 896);                     \
        }                                                                                                     \
      }
#define P_FINISH(V, C)                                                                                        \
      {                                                                                                       \
        float fa[2][4] = {{0.f, 0.f, 0.f, 0.f}, {0.f, 0.f, 0.f, 0.f}}, fb[2][4] = {{0.f, 0.f, 0.f, 0.f}, {0.f, 0.f, 0.f, 0.f}}; \
        _Pragma("unroll") for (int s = 0; s < 8; s++) {                                                       \
          mma1688(fa[s & 1], V[s].x, V[s].y, eye);                                                            \
          mma1688(fb[s & 1], V[s].z, V[s].w, eye);                                                            \
        }                                                                                                     \
        const uint32_t oa0 = bf2_add(hr[2 * C].x, pack_bf16(fa[0][0] + fa[1][0], fa[0][1] + fa[1][1]));       \
        const uint32_t oa1 = bf2_add(hr[2 * C].y, pack_bf16(fa[0][2] + fa[1][2], fa[0][3] + fa[1][3]));       \
        const uint32_t ob0 = bf2_add(hr[2 * C + 1].x, pack_bf16(fb[0][0] + fb[1][0], fb[0][1] + fb[1][1]));   \
        const uint32_t ob1 = bf2_add(hr[2 * C + 1].y, pack_bf16(fb[0][2] + fb[1][2], fb[0][3] + fb[1][3]));   \
        const uint32_t g0 = __shfl_xor_sync(~0u, odd ? oa0 : ob0, 1), g1 = __shfl_xor_sync(~0u, odd ? oa1 : ob1, 1); \
        const int col = 128 * C + 16 * j + coff;                                                              \
        *reinterpret_cast<uint2*>(orow + col) = odd ? make_uint2(g0, ob0) : make_uint2(oa0, g0);              \
        *reinterpret_cast<uint2*>(orow + 16 * DM + col) = odd ? make_uint2(g1, ob1) : make_uint2(oa1, g1);    \
      }
      P_CHECK(v0, 0)
      P_FINISH(v0, 0)
      TTS(24);
      wait_hint(sync + SY_P1 + (lane < 24 ? lane : 0), stamp);
      TTS(27);
      uint2 v3[8];
#pragma unroll
      for (int s = 0; s < 8; s++) { v3[s] = ldx8(p3 + s * 1792); v1[s] = ldx16(pp + 256 + s * 896); v0[s] = ldx16(pp + 512 + s * 896); }
      if (j == 0 && lane < 2) asm volatile("st.relaxed.gpu.global.u32 [%0], %1;" ::"l"(sync + (lane ? SY_EPOCH2 : SY_EPOCH)), "r"(stamp) : "memory");
      P_CHECK(v1, 256)
      P_FINISH(v1, 1)
      P_CHECK(v0, 512)
      P_FINISH(v0, 2)
      {
        uint32_t it = 0;
#pragma unroll 1
        while (true) {
          uint32_t bad = 0;
#pragma unroll
          for (int s = 0; s < 8; s++) bad |= v3[s].x ^ tag;
          if (__all_sync(~0u, (bad & 1) == 0) || spin_expired(it)) break;
#pragma unroll
          for (int s = 0; s < 8; s++) v3[s] = ldx8(p3 + s * 1792);
        }
      }
      TS(13);
      {
        float f[4] = {0.f, 0.f, 0.f, 0.f};
#pragma unroll
        for (int s = 0; s < 8; s++) mma1688(f, v3[s].x, v3[s].y, eye);
        const uint32_t oa = bf2_add(hf ? hr[6].y : hr[6].x, pack_bf16(f[0], f[1]));
        const uint32_t ob2 = bf2_add(hf ? hr[7].y : hr[7].x, pack_bf16(f[2], f[3]));
        const uint32_t g = __shfl_xor_sync(~0u, odd ? oa : ob2, 1);
        const int col = 384 + 16 * (j >> 1) + coff;
        *reinterpret_cast<uint2*>(orow + hf * 16 * DM + col) = odd ? make_uint2(g, ob2) : make_uint2(oa, g);
      }
      TS(14);
    }
  }
  asm volatile("barrier.cluster.arrive.relaxed.aligned;\nbarrier.cluster.wait.aligned;" ::: "memory");
}

typedef CUresult (*EncodeFn)(CUtensorMap*, CUtensorMapDataType, cuuint32_t, void*, const cuuint64_t*, const cuuint64_t*,
                             const cuuint32_t*, const cuuint32_t*, CUtensorMapInterleave, CUtensorMapSwizzle,
                             CUtensorMapL2promotion, CUtensorMapFloatOOBfill);

int encode(EncodeFn fn, CUtensorMap* m, int rank, const void* ptr, const cuuint64_t* dims, const cuuint64_t* strides,
           const cuuint32_t* box) {
  const cuuint32_t es[5] = {1, 1, 1, 1, 1};
  return (int)fn(m, CU_TENSOR_MAP_DATA_TYPE_BFLOAT16, rank, const_cast<void*>(ptr), dims, strides, box, es,
                 CU_TENSOR_MAP_INTERLEAVE_NONE, CU_TENSOR_MAP_SWIZZLE_128B, CU_TENSOR_MAP_L2_PROMOTION_L2_128B,
                 CU_TENSOR_MAP_FLOAT_OOB_FILL_NONE);
}

}

extern "C" void kernel_launch(void* const* d_in, const int* in_sizes, int n_in, void* d_out, int out_size) {
  (void)in_sizes; (void)n_in; (void)out_size;
  static EncodeFn fn = nullptr;
  if (!fn) {
    void* sym = nullptr;
    cudaDriverEntryPointQueryResult st;
    cudaGetDriverEntryPoint("cuTensorMapEncodeTiled", &sym, cudaEnableDefault, &st);
    fn = reinterpret_cast<EncodeFn>(sym);
    cudaFuncSetAttribute(fused_block_kernel, cudaFuncAttributeMaxDynamicSharedMemorySize, SMEM_B);
  }
  Params prm;
  int rc = 0;
  {
    const cuuint64_t dims[4] = {64, SEQ / 2, 7, 2};
    const cuuint64_t str[3] = {2 * DM * 2, 128, DM * 2};
    const cuuint32_t box[4] = {64, 16, 7, 1};
    rc |= encode(fn, &prm.tx, 4, d_in[0], dims, str, box);
  }
  {
    const cuuint64_t dims[2] = {3 * DM, DM};
    const cuuint64_t str[1] = {3 * DM * 2};
    const cuuint32_t box[2] = {56, 112};
    rc |= encode(fn, &prm.tqkv, 2, d_in[1], dims, str, box);
  }
  {
    const cuuint64_t dims[2] = {DM, DM};
    const cuuint64_t str[1] = {DM * 2};
    const cuuint32_t box[2] = {56, 112};
    rc |= encode(fn, &prm.two, 2, d_in[2], dims, str, box);
  }
  {
    const cuuint64_t dims[2] = {DFF, DM};
    const cuuint64_t str[1] = {DFF * 2};
    const cuuint32_t box[2] = {64, 112};
    rc |= encode(fn, &prm.tw1, 2, d_in[4], dims, str, box);
    const cuuint32_t narrow[2] = {32, 112};
    rc |= encode(fn, &prm.tw1n, 2, d_in[4], dims, str, narrow);
  }
  {
    const cuuint64_t dims[2] = {DM, DFF};
    const cuuint64_t str[1] = {DM * 2};
    const cuuint32_t box[2] = {64, 112};
    rc |= encode(fn, &prm.tw2, 2, d_in[5], dims, str, box);
  }
  (void)rc;
  prm.wqkv = d_in[1]; prm.wo = d_in[2]; prm.w1 = d_in[4]; prm.w2 = d_in[5];

  cudaLaunchConfig_t cfg = {};
  cfg.gridDim = dim3(128);
  cfg.blockDim = dim3(NTHREADS);
  cfg.dynamicSmemBytes = SMEM_B;
  cfg.stream = cudaStreamPerThread;
  cudaLaunchAttribute at[1];
  at[0].id = cudaLaunchAttributeClusterDimension;
  at[0].val.clusterDim.x = USE_MC ? 2 : 1;
  at[0].val.clusterDim.y = 1;
  at[0].val.clusterDim.z = 1;
  cfg.attrs = at;
  cfg.numAttrs = USE_MC ? 1 : 0;
  cudaLaunchKernelEx(&cfg, fused_block_kernel, prm, reinterpret_cast<const __nv_bfloat16*>(d_in[0]),
                     reinterpret_cast<__nv_bfloat16*>(d_out));
}
```

```cpp
#include <cuda_runtime.h>
#include <cuda_bf16.h>
#include <cuda.h>
#include <stdint.h>

namespace {

constexpr int SEQ = 2048;
constexpr int DM = 448;
constexpr int DFF = 1792;
constexpr int TILE_B = 14336;
constexpr int STAGE_B = 2 * TILE_B;
constexpr int NST = 8;
constexpr int NSTAGE_TOTAL = 27;
__host__ __device__ constexpr int slot_of(int i) {
  return i < 4 ? (i & 1) : i < 8 ? i : i < 10 ? i - 6 : i == 10 ? 0 : "\4\5\6\7\2\3\0\1"[(i - 11) & 7];
}
__host__ __device__ constexpr int use_of(int i) {
  return i < 2 ? 0 : i < 4 ? 1 : i < 10 ? 0 : i == 10 ? 2 : (slot_of(i) < 2 ? 2 : 0) + 1 + (i - 11) / 8;
}
__host__ __device__ constexpr int full_bar(int i) { return i == 2 ? 22 : i == 3 ? 23 : slot_of(i); }
__host__ __device__ constexpr int full_par(int i) {
  return (i == 2 || i == 3) ? 0 : (slot_of(i) == 0 && i >= 10) ? (use_of(i) - 1) & 1 : (slot_of(i) == 1 && i >= 10) ? (use_of(i) - 2) & 1 : use_of(i) & 1;
}
__host__ __device__ constexpr int stage_bytes(int i) {
  return i < 4 ? 28672 : i < 12 ? 2 * 112 * 112 : (i >= 16 && i < 20) ? 112 * (128 + 64) : 28672;
}
constexpr int HAND_SLOT = 1;
constexpr int HAND_OFF = HAND_SLOT * STAGE_B;
constexpr int ZERO_OFF = NST * STAGE_B;
constexpr int ZERO_B = 2048;
constexpr int BAR_OFF = ZERO_OFF + ZERO_B;
constexpr int SMEM_B = BAR_OFF + 256;
constexpr int NTHREADS = 384;
constexpr uint32_t SPIN_LIMIT = 1u << 20;

__device__ uint4 g_O[2][128 * 8 * 112];
__device__ uint4 g_H[2][128 * 8 * 120];
__device__ uint4 g_halo[2][16 * 2 * 8 * 128];
__device__ uint4 g_P[128 * 8 * 896];
__device__ uint32_t g_sync[128 * 64];
constexpr int SY_O = 0, SY_H = 8, SY_EPOCH = 24, SY_EPOCH2 = 32, SY_P3 = 56;

__device__ __forceinline__ uint32_t smem_u32(const void* p) { return (uint32_t)__cvta_generic_to_shared(p); }

__device__ __forceinline__ void mbar_init(uint32_t bar, uint32_t cnt) {
  asm volatile("mbarrier.init.shared::cta.b64 [%0], %1;" ::"r"(bar), "r"(cnt) : "memory");
}
__device__ __forceinline__ void mbar_expect_tx(uint32_t bar, uint32_t bytes) {
  asm volatile("mbarrier.arrive.expect_tx.shared::cta.b64 _, [%0], %1;" ::"r"(bar), "r"(bytes) : "memory");
}
__device__ __forceinline__ void mbar_arrive(uint32_t bar, uint32_t cnt) {
  asm volatile("mbarrier.arrive.shared::cta.b64 _, [%0], %1;" ::"r"(bar), "r"(cnt) : "memory");
}
__device__ __forceinline__ uint32_t map_to_cta(uint32_t addr, uint32_t cta) {
  uint32_t r;
  asm("mapa.shared::cluster.u32 %0, %1, %2;" : "=r"(r) : "r"(addr), "r"(cta));
  return r;
}
__device__ __forceinline__ bool mbar_try(uint32_t bar, uint32_t parity) {
  uint32_t ok;
  asm volatile(
      "{\n.reg .pred p;\nmbarrier.try_wait.parity.shared::cta.b64 p, [%1], %2;\nselp.u32 %0, 1, 0, p;\n}"
      : "=r"(ok)
      : "r"(bar), "r"(parity)
      : "memory");
  return ok != 0;
}
__device__ __forceinline__ void mbar_wait(uint32_t bar, uint32_t parity) {
  for (uint32_t it = 0; !mbar_try(bar, parity) && it < SPIN_LIMIT; it++) {}
}

template <int DIM>
__device__ __forceinline__ void tma_load(uint32_t dst, const CUtensorMap* tm, uint32_t bar, int c0, int c1, int c2, int c3) {
  uint64_t d = reinterpret_cast<uint64_t>(tm);
  if constexpr (DIM == 2)
    asm volatile("cp.async.bulk.tensor.2d.shared::cluster.global.mbarrier::complete_tx::bytes [%0], [%1, {%3, %4}], [%2];" ::"r"(dst),
                 "l"(d), "r"(bar), "r"(c0), "r"(c1)
                 : "memory");
  if constexpr (DIM == 3)
    asm volatile("cp.async.bulk.tensor.3d.shared::cluster.global.mbarrier::complete_tx::bytes [%0], [%1, {%3, %4, %5}], [%2];" ::"r"(dst),
                 "l"(d), "r"(bar), "r"(c0), "r"(c1), "r"(c2)
                 : "memory");
  if constexpr (DIM == 4)
    asm volatile("cp.async.bulk.tensor.4d.shared::cluster.global.mbarrier::complete_tx::bytes [%0], [%1, {%3, %4, %5, %6}], [%2];" ::"r"(dst),
                 "l"(d), "r"(bar), "r"(c0), "r"(c1), "r"(c2), "r"(c3)
                 : "memory");
}
template <int DIM>
__device__ __forceinline__ void tma_load_mc(uint32_t dst, const CUtensorMap* tm, uint32_t bar, int c0, int c1, int c2) {
  uint64_t d = reinterpret_cast<uint64_t>(tm);
  const uint16_t mask = 3;
  if constexpr (DIM == 2)
    asm volatile(
        "cp.async.bulk.tensor.2d.shared::cluster.global.mbarrier::complete_tx::bytes.multicast::cluster [%0], [%1, {%3, %4}], [%2], %5;" ::"r"(dst),
        "l"(d), "r"(bar), "r"(c0), "r"(c1), "h"(mask)
        : "memory");
  if constexpr (DIM == 3)
    asm volatile(
        "cp.async.bulk.tensor.3d.shared::cluster.global.mbarrier::complete_tx::bytes.multicast::cluster [%0], [%1, {%3, %4, %5}], [%2], %6;" ::"r"(dst),
        "l"(d), "r"(bar), "r"(c0), "r"(c1), "r"(c2), "h"(mask)
        : "memory");
}
__device__ __forceinline__ void bulk_store(void* dst, uint32_t src, uint32_t bytes) {
  asm volatile("cp.async.bulk.global.shared::cta.bulk_group [%0], [%1], %2;" ::"l"(dst), "r"(src), "r"(bytes) : "memory");
}

__device__ __forceinline__ uint4 ldx16(const void* p) {
  uint4 v;
  asm volatile(
      "{\n.reg .b128 t;\n.reg .b64 lo, hi;\nld.relaxed.gpu.global.b128 t, [%4];\nmov.b128 {lo, hi}, t;\n"
      "mov.b64 {%0, %1}, lo;\nmov.b64 {%2, %3}, hi;\n}"
      : "=r"(v.x), "=r"(v.y), "=r"(v.z), "=r"(v.w)
      : "l"(p)
      : "memory");
  return v;
}
__device__ __forceinline__ void stx16(void* p, uint32_t a, uint32_t b, uint32_t c, uint32_t d) {
  asm volatile(
      "{\n.reg .b128 t;\n.reg .b64 lo, hi;\nmov.b64 lo, {%1, %2};\nmov.b64 hi, {%3, %4};\nmov.b128 t, {lo, hi};\n"
      "st.relaxed.gpu.global.b128 [%0], t;\n}" ::"l"(p),
      "r"(a), "r"(b), "r"(c), "r"(d)
      : "memory");
}
__device__ __forceinline__ uint2 ldx8(const void* p) {
  uint2 v;
  asm volatile("{\n.reg .b64 t;\nld.relaxed.gpu.global.b64 t, [%2];\nmov.b64 {%0, %1}, t;\n}" : "=r"(v.x), "=r"(v.y) : "l"(p) : "memory");
  return v;
}
__device__ __forceinline__ void stx8(void* p, uint32_t a, uint32_t b) {
  asm volatile("{\n.reg .b64 t;\nmov.b64 t, {%1, %2};\nst.relaxed.gpu.global.b64 [%0], t;\n}" ::"l"(p), "r"(a), "r"(b) : "memory");
}
__device__ __forceinline__ uint32_t nz(uint32_t w) { return max(w, 1u); }
__device__ __forceinline__ bool spin_expired(uint32_t& it) { return ++it > SPIN_LIMIT; }

__device__ __forceinline__ uint32_t pack_bf16(float lo, float hi) {
  uint32_t r;
  asm("cvt.rn.bf16x2.f32 %0, %1, %2;" : "=r"(r) : "f"(hi), "f"(lo));
  return r;
}
__device__ __forceinline__ uint32_t pack_bf16_relu(float lo, float hi) {
  uint32_t r;
  asm("cvt.rn.relu.bf16x2.f32 %0, %1, %2;" : "=r"(r) : "f"(hi), "f"(lo));
  return r;
}
__device__ __forceinline__ float bf_lo(uint32_t w) { return __uint_as_float(w << 16); }
__device__ __forceinline__ float bf_hi(uint32_t w) { return __uint_as_float(w & 0xffff0000u); }
__device__ __forceinline__ uint32_t bf2_sub(uint32_t a, uint32_t b) {
  uint32_t r;
  asm("sub.rn.bf16x2 %0, %1, %2;" : "=r"(r) : "r"(a), "r"(b));
  return r;
}
__device__ __forceinline__ uint32_t bf2_add(uint32_t a, uint32_t b) {
  uint32_t r;
  asm("add.rn.bf16x2 %0, %1, %2;" : "=r"(r) : "r"(a), "r"(b));
  return r;
}
__device__ __forceinline__ void mma16816(float (&d)[4], uint32_t a0, uint32_t a1, uint32_t a2, uint32_t a3, uint32_t b0, uint32_t b1) {
  asm("mma.sync.aligned.m16n8k16.row.col.f32.bf16.bf16.f32 {%0,%1,%2,%3}, {%4,%5,%6,%7}, {%8,%9}, {%0,%1,%2,%3};"
      : "+f"(d[0]), "+f"(d[1]), "+f"(d[2]), "+f"(d[3])
      : "r"(a0), "r"(a1), "r"(a2), "r"(a3), "r"(b0), "r"(b1));
}
__device__ __forceinline__ void mma1688(float (&d)[4], uint32_t a0, uint32_t a1, uint32_t b0) {
  asm("mma.sync.aligned.m16n8k8.row.col.f32.bf16.bf16.f32 {%0,%1,%2,%3}, {%4,%5}, {%6}, {%0,%1,%2,%3};"
      : "+f"(d[0]), "+f"(d[1]), "+f"(d[2]), "+f"(d[3])
      : "r"(a0), "r"(a1), "r"(b0));
}
__device__ __forceinline__ uint32_t movmat(uint32_t a) {
  uint32_t d;
  asm volatile("movmatrix.sync.aligned.m8n8.trans.b16 %0, %1;" : "=r"(d) : "r"(a));
  return d;
}
__device__ __forceinline__ float ex2(float x) {
  float y;
  asm("ex2.approx.ftz.f32 %0, %1;" : "=f"(y) : "f"(x));
  return y;
}

__device__ __forceinline__ float rcp(float x) {
  float y;
  asm("rcp.approx.ftz.f32 %0, %1;" : "=f"(y) : "f"(x));
  return y;
}

__device__ __forceinline__ void wg_fence() { asm volatile("wgmma.fence.sync.aligned;" ::: "memory"); }
__device__ __forceinline__ void wg_commit() { asm volatile("wgmma.commit_group.sync.aligned;" ::: "memory"); }
template <int N>
__device__ __forceinline__ void wg_wait() {
  asm volatile("wgmma.wait_group.sync.aligned %0;" ::"n"(N) : "memory");
}
template <int N>
__device__ __forceinline__ void reg_fence(float (&d)[N]) {
#pragma unroll
  for (int i = 0; i < N; i++) asm volatile("" : "+f"(d[i])::"memory");
}

__device__ __forceinline__ uint32_t opaque(uint32_t v) {
  uint32_t r;
  asm volatile("mov.u32 %0, %1;" : "=r"(r) : "r"(v));
  return r;
}

constexpr uint32_t DESC_LBO = (uint32_t)(TILE_B >> 4) << 16;
constexpr uint32_t DESC_HI = (1024u >> 4) | (1u << 30);
constexpr uint32_t DESC_HI_FAR = (7168u >> 4) | (1u << 30);

#define WG_ACC4(d, i) "+f"(d[i]), "+f"(d[i + 1]), "+f"(d[i + 2]), "+f"(d[i + 3])
#define WG_OUT4(d, i) "=f"(d[i]), "=f"(d[i + 1]), "=f"(d[i + 2]), "=f"(d[i + 3])

__device__ __forceinline__ void wgmma_n56(float (&d)[28], uint32_t a0, uint32_t a1, uint32_t a2, uint32_t a3, uint32_t lo, uint32_t hi) {
  asm volatile(
      "{\n.reg .b64 dsc;\n.reg .pred p;\n"
      "mov.b64 dsc, {%32, %33};\nsetp.ne.b32 p, 1, 0;\n"
      "wgmma.mma_async.sync.aligned.m64n56k16.f32.bf16.bf16 "
      "{%0, %1, %2, %3, %4, %5, %6, %7, %8, %9, %10, %11, %12, %13, %14, %15, "
      "%16, %17, %18, %19, %20, %21, %22, %23, %24, %25, %26, %27}, "
      "{%28, %29, %30, %31}, dsc, p, 1, 1, 1;\n}"
      : WG_ACC4(d, 0), WG_ACC4(d, 4), WG_ACC4(d, 8), WG_ACC4(d, 12), WG_ACC4(d, 16), WG_ACC4(d, 20), WG_ACC4(d, 24)
      : "r"(a0), "r"(a1), "r"(a2), "r"(a3), "r"(lo), "r"(hi));
}
__device__ __forceinline__ void wgmma_n56_init(float (&d)[28], uint32_t a0, uint32_t a1, uint32_t a2, uint32_t a3, uint32_t lo, uint32_t hi) {
  asm volatile(
      "{\n.reg .b64 dsc;\n.reg .pred p;\n"
      "mov.b64 dsc, {%32, %33};\nsetp.ne.b32 p, 0, 0;\n"
      "wgmma.mma_async.sync.aligned.m64n56k16.f32.bf16.bf16 "
      "{%0, %1, %2, %3, %4, %5, %6, %7, %8, %9, %10, %11, %12, %13, %14, %15, "
      "%16, %17, %18, %19, %20, %21, %22, %23, %24, %25, %26, %27}, "
      "{%28, %29, %30, %31}, dsc, p, 1, 1, 1;\n}"
      : WG_OUT4(d, 0), WG_OUT4(d, 4), WG_OUT4(d, 8), WG_OUT4(d, 12), WG_OUT4(d, 16), WG_OUT4(d, 20), WG_OUT4(d, 24)
      : "r"(a0), "r"(a1), "r"(a2), "r"(a3), "r"(lo), "r"(hi));
}
__device__ __forceinline__ void wgmma_n64(float (&d)[32], uint32_t a0, uint32_t a1, uint32_t a2, uint32_t a3, uint32_t lo, uint32_t hi) {
  asm volatile(
      "{\n.reg .b64 dsc;\n.reg .pred p;\n"
      "mov.b64 dsc, {%36, %37};\nsetp.ne.b32 p, 1, 0;\n"
      "wgmma.mma_async.sync.aligned.m64n64k16.f32.bf16.bf16 "
      "{%0, %1, %2, %3, %4, %5, %6, %7, %8, %9, %10, %11, %12, %13, %14, %15, "
      "%16, %17, %18, %19, %20, %21, %22, %23, %24, %25, %26, %27, %28, %29, %30, %31}, "
      "{%32, %33, %34, %35}, dsc, p, 1, 1, 1;\n}"
      : WG_ACC4(d, 0), WG_ACC4(d, 4), WG_ACC4(d, 8), WG_ACC4(d, 12), WG_ACC4(d, 16), WG_ACC4(d, 20), WG_ACC4(d, 24), WG_ACC4(d, 28)
      : "r"(a0), "r"(a1), "r"(a2), "r"(a3), "r"(lo), "r"(hi));
}
__device__ __forceinline__ void wgmma_n64_init(float (&d)[32], uint32_t a0, uint32_t a1, uint32_t a2, uint32_t a3, uint32_t lo, uint32_t hi) {
  asm volatile(
      "{\n.reg .b64 dsc;\n.reg .pred p;\n"
      "mov.b64 dsc, {%36, %37};\nsetp.ne.b32 p, 0, 0;\n"
      "wgmma.mma_async.sync.aligned.m64n64k16.f32.bf16.bf16 "
      "{%0, %1, %2, %3, %4, %5, %6, %7, %8, %9, %10, %11, %12, %13, %14, %15, "
      "%16, %17, %18, %19, %20, %21, %22, %23, %24, %25, %26, %27, %28, %29, %30, %31}, "
      "{%32, %33, %34, %35}, dsc, p, 1, 1, 1;\n}"
      : WG_OUT4(d, 0), WG_OUT4(d, 4), WG_OUT4(d, 8), WG_OUT4(d, 12), WG_OUT4(d, 16), WG_OUT4(d, 20), WG_OUT4(d, 24), WG_OUT4(d, 28)
      : "r"(a0), "r"(a1), "r"(a2), "r"(a3), "r"(lo), "r"(hi));
}
__device__ __forceinline__ void wgmma_n96(float (&d)[48], uint32_t a0, uint32_t a1, uint32_t a2, uint32_t a3, uint32_t lo, uint32_t hi) {
  asm volatile(
      "{\n.reg .b64 dsc;\n.reg .pred p;\n"
      "mov.b64 dsc, {%52, %53};\nsetp.ne.b32 p, 1, 0;\n"
      "wgmma.mma_async.sync.aligned.m64n96k16.f32.bf16.bf16 "
      "{%0, %1, %2, %3, %4, %5, %6, %7, %8, %9, %10, %11, %12, %13, %14, %15, "
      "%16, %17, %18, %19, %20, %21, %22, %23, %24, %25, %26, %27, %28, %29, %30, %31, "
      "%32, %33, %34, %35, %36, %37, %38, %39, %40, %41, %42, %43, %44, %45, %46, %47}, "
      "{%48, %49, %50, %51}, dsc, p, 1, 1, 1;\n}"
      : WG_ACC4(d, 0), WG_ACC4(d, 4), WG_ACC4(d, 8), WG_ACC4(d, 12), WG_ACC4(d, 16), WG_ACC4(d, 20), WG_ACC4(d, 24), WG_ACC4(d, 28), WG_ACC4(d, 32), WG_ACC4(d, 36), WG_ACC4(d, 40), WG_ACC4(d, 44)
      : "r"(a0), "r"(a1), "r"(a2), "r"(a3), "r"(lo), "r"(hi));
}
__device__ __forceinline__ void wgmma_n96_init(float (&d)[48], uint32_t a0, uint32_t a1, uint32_t a2, uint32_t a3, uint32_t lo, uint32_t hi) {
  asm volatile(
      "{\n.reg .b64 dsc;\n.reg .pred p;\n"
      "mov.b64 dsc, {%52, %53};\nsetp.ne.b32 p, 0, 0;\n"
      "wgmma.mma_async.sync.aligned.m64n96k16.f32.bf16.bf16 "
      "{%0, %1, %2, %3, %4, %5, %6, %7, %8, %9, %10, %11, %12, %13, %14, %15, "
      "%16, %17, %18, %19, %20, %21, %22, %23, %24, %25, %26, %27, %28, %29, %30, %31, "
      "%32, %33, %34, %35, %36, %37, %38, %39, %40, %41, %42, %43, %44, %45, %46, %47}, "
      "{%48, %49, %50, %51}, dsc, p, 1, 1, 1;\n}"
      : WG_OUT4(d, 0), WG_OUT4(d, 4), WG_OUT4(d, 8), WG_OUT4(d, 12), WG_OUT4(d, 16), WG_OUT4(d, 20), WG_OUT4(d, 24), WG_OUT4(d, 28), WG_OUT4(d, 32), WG_OUT4(d, 36), WG_OUT4(d, 40), WG_OUT4(d, 44)
      : "r"(a0), "r"(a1), "r"(a2), "r"(a3), "r"(lo), "r"(hi));
}
__device__ __forceinline__ void wgmma_n120(float (&d)[60], uint32_t a0, uint32_t a1, uint32_t a2, uint32_t a3, uint32_t lo, uint32_t hi) {
  asm volatile(
      "{\n.reg .b64 dsc;\n.reg .pred p;\n"
      "mov.b64 dsc, {%64, %65};\nsetp.ne.b32 p, 1, 0;\n"
      "wgmma.mma_async.sync.aligned.m64n120k16.f32.bf16.bf16 "
      "{%0, %1, %2, %3, %4, %5, %6, %7, %8, %9, %10, %11, %12, %13, %14, %15, "
      "%16, %17, %18, %19, %20, %21, %22, %23, %24, %25, %26, %27, %28, %29, %30, %31, "
      "%32, %33, %34, %35, %36, %37, %38, %39, %40, %41, %42, %43, %44, %45, %46, %47, "
      "%48, %49, %50, %51, %52, %53, %54, %55, %56, %57, %58, %59}, "
      "{%60, %61, %62, %63}, dsc, p, 1, 1, 1;\n}"
      : WG_ACC4(d, 0), WG_ACC4(d, 4), WG_ACC4(d, 8), WG_ACC4(d, 12), WG_ACC4(d, 16), WG_ACC4(d, 20), WG_ACC4(d, 24), WG_ACC4(d, 28), WG_ACC4(d, 32), WG_ACC4(d, 36), WG_ACC4(d, 40), WG_ACC4(d, 44), WG_ACC4(d, 48), WG_ACC4(d, 52), WG_ACC4(d, 56)
      : "r"(a0), "r"(a1), "r"(a2), "r"(a3), "r"(lo), "r"(hi));
}
__device__ __forceinline__ void wgmma_n120_init(float (&d)[60], uint32_t a0, uint32_t a1, uint32_t a2, uint32_t a3, uint32_t lo, uint32_t hi) {
  asm volatile(
      "{\n.reg .b64 dsc;\n.reg .pred p;\n"
      "mov.b64 dsc, {%64, %65};\nsetp.ne.b32 p, 0, 0;\n"
      "wgmma.mma_async.sync.aligned.m64n120k16.f32.bf16.bf16 "
      "{%0, %1, %2, %3, %4, %5, %6, %7, %8, %9, %10, %11, %12, %13, %14, %15, "
      "%16, %17, %18, %19, %20, %21, %22, %23, %24, %25, %26, %27, %28, %29, %30, %31, "
      "%32, %33, %34, %35, %36, %37, %38, %39, %40, %41, %42, %43, %44, %45, %46, %47, "
      "%48, %49, %50, %51, %52, %53, %54, %55, %56, %57, %58, %59}, "
      "{%60, %61, %62, %63}, dsc, p, 1, 1, 1;\n}"
      : WG_OUT4(d, 0), WG_OUT4(d, 4), WG_OUT4(d, 8), WG_OUT4(d, 12), WG_OUT4(d, 16), WG_OUT4(d, 20), WG_OUT4(d, 24), WG_OUT4(d, 28), WG_OUT4(d, 32), WG_OUT4(d, 36), WG_OUT4(d, 40), WG_OUT4(d, 44), WG_OUT4(d, 48), WG_OUT4(d, 52), WG_OUT4(d, 56)
      : "r"(a0), "r"(a1), "r"(a2), "r"(a3), "r"(lo), "r"(hi));
}
__device__ __forceinline__ void wgmma_n128(float (&d)[64], uint32_t a0, uint32_t a1, uint32_t a2, uint32_t a3, uint32_t lo, uint32_t hi) {
  asm volatile(
      "{\n.reg .b64 dsc;\n.reg .pred p;\n"
      "mov.b64 dsc, {%68, %69};\nsetp.ne.b32 p, 1, 0;\n"
      "wgmma.mma_async.sync.aligned.m64n128k16.f32.bf16.bf16 "
      "{%0, %1, %2, %3, %4, %5, %6, %7, %8, %9, %10, %11, %12, %13, %14, %15, "
      "%16, %17, %18, %19, %20, %21, %22, %23, %24, %25, %26, %27, %28, %29, %30, %31, "
      "%32, %33, %34, %35, %36, %37, %38, %39, %40, %41, %42, %43, %44, %45, %46, %47, "
      "%48, %49, %50, %51, %52, %53, %54, %55, %56, %57, %58, %59, %60, %61, %62, %63}, "
      "{%64, %65, %66, %67}, dsc, p, 1, 1, 1;\n}"
      : WG_ACC4(d, 0), WG_ACC4(d, 4), WG_ACC4(d, 8), WG_ACC4(d, 12), WG_ACC4(d, 16), WG_ACC4(d, 20), WG_ACC4(d, 24), WG_ACC4(d, 28), WG_ACC4(d, 32), WG_ACC4(d, 36), WG_ACC4(d, 40), WG_ACC4(d, 44), WG_ACC4(d, 48), WG_ACC4(d, 52), WG_ACC4(d, 56), WG_ACC4(d, 60)
      : "r"(a0), "r"(a1), "r"(a2), "r"(a3), "r"(lo), "r"(hi));
}
__device__ __forceinline__ void wgmma_n128_init(float (&d)[64], uint32_t a0, uint32_t a1, uint32_t a2, uint32_t a3, uint32_t lo, uint32_t hi) {
  asm volatile(
      "{\n.reg .b64 dsc;\n.reg .pred p;\n"
      "mov.b64 dsc, {%68, %69};\nsetp.ne.b32 p, 0, 0;\n"
      "wgmma.mma_async.sync.aligned.m64n128k16.f32.bf16.bf16 "
      "{%0, %1, %2, %3, %4, %5, %6, %7, %8, %9, %10, %11, %12, %13, %14, %15, "
      "%16, %17, %18, %19, %20, %21, %22, %23, %24, %25, %26, %27, %28, %29, %30, %31, "
      "%32, %33, %34, %35, %36, %37, %38, %39, %40, %41, %42, %43, %44, %45, %46, %47, "
      "%48, %49, %50, %51, %52, %53, %54, %55, %56, %57, %58, %59, %60, %61, %62, %63}, "
      "{%64, %65, %66, %67}, dsc, p, 1, 1, 1;\n}"
      : WG_OUT4(d, 0), WG_OUT4(d, 4), WG_OUT4(d, 8), WG_OUT4(d, 12), WG_OUT4(d, 16), WG_OUT4(d, 20), WG_OUT4(d, 24), WG_OUT4(d, 28), WG_OUT4(d, 32), WG_OUT4(d, 36), WG_OUT4(d, 40), WG_OUT4(d, 44), WG_OUT4(d, 48), WG_OUT4(d, 52), WG_OUT4(d, 56), WG_OUT4(d, 60)
      : "r"(a0), "r"(a1), "r"(a2), "r"(a3), "r"(lo), "r"(hi));
}

template <int S0, int NS>
__device__ __forceinline__ void center_part(uint32_t (&A)[112], uint32_t m0, uint32_t m1) {
#pragma unroll
  for (int i = 4 * S0; i < 4 * (S0 + NS); i++) A[i] = bf2_sub(A[i], (i & 1) ? m1 : m0);
}
__device__ __forceinline__ void row_means(uint32_t (&A)[112], uint32_t& m0, uint32_t& m1, float& dm0, float& dm1) {
  float c[14][4];
#pragma unroll
  for (int i = 0; i < 14; i++) c[i][0] = c[i][1] = c[i][2] = c[i][3] = 0.f;
#pragma unroll
  for (int s = 0; s < 28; s++) mma16816(c[s % 14], A[4 * s], A[4 * s + 1], A[4 * s + 2], A[4 * s + 3], 0x3f803f80u, 0x3f803f80u);
  float mu0 = 0.f, mu1 = 0.f;
  {
    float t0[7], t1[7];
#pragma unroll
    for (int i = 0; i < 7; i++) { t0[i] = c[i][0] + c[i + 7][0]; t1[i] = c[i][2] + c[i + 7][2]; }
    mu0 = (((t0[0] + t0[1]) + (t0[2] + t0[3])) + ((t0[4] + t0[5]) + t0[6])) * (1.f / DM);
    mu1 = (((t1[0] + t1[1]) + (t1[2] + t1[3])) + ((t1[4] + t1[5]) + t1[6])) * (1.f / DM);
  }
  m0 = pack_bf16(mu0, mu0);
  m1 = pack_bf16(mu1, mu1);
  dm0 = mu0 - bf_lo(m0);
  dm1 = mu1 - bf_lo(m1);
}
template <int S0, int NS>
__device__ __forceinline__ void sumsq_part(const uint32_t (&A)[112], float (&q)[2]) {
#pragma unroll
  for (int e = 0; e < 4; e++) {
    uint32_t acc;
    asm volatile("mul.rn.bf16x2 %0, %1, %1;" : "=r"(acc) : "r"(A[4 * S0 + e]));
#pragma unroll
    for (int s = S0 + 1; s < S0 + NS; s++) asm volatile("fma.rn.bf16x2 %0, %1, %1, %0;" : "+r"(acc) : "r"(A[4 * s + e]));
    q[e & 1] += bf_lo(acc) + bf_hi(acc);
  }
}
__device__ __forceinline__ float rstd_of(float sumsq, float dm) {
  return rsqrtf(fmaxf(sumsq * (1.f / DM) - dm * dm, 0.f) + 1e-5f);
}
__device__ __forceinline__ void finish_rstd(const float (&q)[2], float dm0, float dm1, float& rs0, float& rs1) {
  float s0 = q[0], s1 = q[1];
  s0 += __shfl_xor_sync(~0u, s0, 1);
  s1 += __shfl_xor_sync(~0u, s1, 1);
  s0 += __shfl_xor_sync(~0u, s0, 2);
  s1 += __shfl_xor_sync(~0u, s1, 2);
  rs0 = rstd_of(s0, dm0);
  rs1 = rstd_of(s1, dm1);
}

__device__ __forceinline__ constexpr int xword(int sl, int i) {
  return 4 * (7 * (sl >> 1) + ((sl & 1) ? 4 : 0) + i);
}
__device__ __forceinline__ constexpr int xsingle(int sl) { return 4 * (7 * (sl >> 1) + 3) + 2 * (sl & 1); }
template <int T, int STRIDE>
__device__ __forceinline__ void load_xtile(uint32_t (&A)[112], const char* base, int lane) {
#pragma unroll
  for (int sl = 2 * T; sl < 2 * T + 2; sl++) {
    const char* p = base + sl * STRIDE;
#pragma unroll
    for (int i = 0; i < 3; i++) {
      uint4 v = ldx16(p + i * 512 + lane * 16);
      A[xword(sl, i)] = v.x; A[xword(sl, i) + 1] = v.y; A[xword(sl, i) + 2] = v.z; A[xword(sl, i) + 3] = v.w;
    }
    uint2 v3 = ldx8(p + 1536 + lane * 8);
    A[xsingle(sl)] = v3.x; A[xsingle(sl) + 1] = v3.y;
  }
}
template <int T>
__device__ __forceinline__ bool xtile_ok(const uint32_t (&A)[112]) {
  uint32_t m = min(min(A[xword(2 * T, 0)], A[xword(2 * T, 1)]), min(A[xword(2 * T, 2)], A[xsingle(2 * T)]));
  m = min(m, min(min(A[xword(2 * T + 1, 0)], A[xword(2 * T + 1, 1)]), min(A[xword(2 * T + 1, 2)], A[xsingle(2 * T + 1)])));
  return __all_sync(~0u, m != 0);
}
template <int T, int STRIDE>
__device__ __forceinline__ void check_xtile(uint32_t (&A)[112], const char* base, int lane) {
  if (__builtin_expect(!xtile_ok<T>(A), 0)) {
    uint32_t it = 0;
#pragma unroll 1
    do {
      load_xtile<T, STRIDE>(A, base, lane);
    } while (!xtile_ok<T>(A) && !spin_expired(it));
  }
}
__device__ __forceinline__ uint32_t* halo_hint(int rb, int p, int j) {
  return g_sync + ((rb * 2 + p) * 4 + 1 + (j >> 2)) * 64 + 25 + (j & 3);
}
__device__ __forceinline__ void wait_hint(const uint32_t* hint, uint32_t want) {
  uint32_t it = 0;
#pragma unroll 1
  while (true) {
    uint32_t v;
    asm volatile("ld.relaxed.gpu.global.u32 %0, [%1];" : "=r"(v) : "l"(hint) : "memory");
    if (__all_sync(~0u, v == want) || spin_expired(it)) break;
  }
}
__device__ __forceinline__ void post_hint(uint32_t* hint, uint32_t value, int lane) {
  __syncwarp();
  if (lane == 0) asm volatile("st.relaxed.gpu.global.u32 [%0], %1;" ::"l"(hint), "r"(value) : "memory");
}
__device__ __forceinline__ void store_slice(uint4* slice, const uint32_t (&w)[14], int lane) {
  char* p = reinterpret_cast<char*>(slice);
  stx16(p + lane * 16, nz(w[0]), w[1], w[2], w[3]);
  stx16(p + 512 + lane * 16, nz(w[4]), w[5], w[6], w[7]);
  stx16(p + 1024 + lane * 16, nz(w[8]), w[9], w[10], w[11]);
  stx8(p + 1536 + lane * 8, nz(w[12]), w[13]);
}
template <int KS>
__device__ __forceinline__ constexpr uint32_t xoff() {
  return KS < 4 ? 2048u * KS : 7168u + 2048u * (KS - 4);
}

__device__ __forceinline__ uint2 load_h_block(const char* htile, int b, int lane) {
  int sl = b / 7, i = b - sl * 7;
  const char* p = htile + sl * 1920 + (i < 6 ? (i >> 1) * 512 + lane * 16 + (i & 1) * 8 : 1536 + lane * 8);
  return ldx8(p);
}

struct Params {
  CUtensorMap tx, tqkv, two, tw1, tw1n, tw2;
};

template <int IDX>
__device__ __forceinline__ void wait_stage(uint32_t bars) {
  mbar_wait(bars + full_bar(IDX) * 8, full_par(IDX));
}
__device__ __forceinline__ void release_stage(uint32_t bars, uint32_t pbars, int slot, uint32_t cnt, int lane) {
  __syncwarp();
  if (lane == 0) {
    mbar_arrive(bars + (NST + slot) * 8, cnt);
    asm volatile("mbarrier.arrive.shared::cluster.b64 _, [%0], %1;" ::"r"(pbars + (NST + slot) * 8), "r"(cnt) : "memory");
  }
}

template <int IDX>
__device__ __forceinline__ void issue_weight_tile(const Params& prm, int t, int j, uint32_t dst, uint32_t bar) {
  const CUtensorMap* tm;
  int c0, c1;
  if constexpr (IDX < 8) {
    tm = &prm.tqkv; c0 = DM * (1 + t) + 56 * j; c1 = 112 * (IDX - 4);
  } else if constexpr (IDX < 10) {
    tm = &prm.tqkv; c0 = 56 * j; c1 = 112 * (2 * (IDX - 8) + t);
  } else if constexpr (IDX < 12) {
    tm = &prm.two; c0 = 56 * j; c1 = 112 * (2 * (IDX - 10) + t);
  } else if constexpr (IDX < 20) {
    tm = (IDX >= 16 && t == 1) ? &prm.tw1n : &prm.tw1;
    c0 = 224 * j + 128 * ((IDX - 12) >> 2) + 64 * t; c1 = 112 * ((IDX - 12) & 3);
  } else if constexpr (IDX < 24) {
    tm = &prm.tw2; c0 = 128 * ((IDX - 20) >> 1) + 64 * t; c1 = 224 * j + 112 * ((IDX - 20) & 1);
  } else {
    tm = &prm.tw2; c0 = 256 + 64 * (IDX - 24); c1 = 224 * j + 112 * t;
  }
  tma_load_mc<2>(dst, tm, bar, c0, c1, 0);
}
template <int IDX>
__device__ __forceinline__ void produce_stage(const Params& prm, uint32_t sbase, uint32_t bars, int rb, int j, int crank) {
  constexpr int slot = slot_of(IDX);
  const uint32_t full = bars + full_bar(IDX) * 8;
  constexpr int prev = (slot == 1 && IDX >= 18) ? use_of(IDX) - 2 : use_of(IDX) - 1;
  if constexpr (prev >= 0) mbar_wait(bars + (NST + slot) * 8, prev & 1);
  if constexpr (IDX == 18) mbar_wait(bars + 25 * 8, 0);
  const uint32_t dst = sbase + slot * STAGE_B;
  mbar_expect_tx(full, stage_bytes(IDX));
  if constexpr (IDX < 4) {
    constexpr int p = IDX >> 1, w0 = (IDX & 1) * 2;
    tma_load<4>(dst, &prm.tx, full, 0, 64 * rb + 16 * w0, 0, p);
    tma_load<4>(dst + TILE_B, &prm.tx, full, 0, 64 * rb + 16 * (w0 + 1), 0, p);
  } else {
    issue_weight_tile<IDX>(prm, crank, j, dst + crank * TILE_B, full);
  }
}
template <int IDX>
__device__ __forceinline__ void produce_from(const Params& prm, uint32_t sbase, uint32_t bars, int rb, int j, int crank) {
  if constexpr (IDX < NSTAGE_TOTAL) {
    produce_stage<IDX>(prm, sbase, bars, rb, j, crank);
    produce_from<IDX + 1>(prm, sbase, bars, rb, j, crank);
  }
}
__device__ __forceinline__ bool elect_one() {
  uint32_t pred;
  asm volatile("{\n.reg .pred p;\nelect.sync _|p, 0xffffffff;\nselp.u32 %0, 1, 0, p;\n}" : "=r"(pred));
  return pred != 0;
}

__global__ void __launch_bounds__(NTHREADS, 1)
fused_block_kernel(const __grid_constant__ Params prm, const __nv_bfloat16* __restrict__ x, __nv_bfloat16* __restrict__ out) {
  extern __shared__ __align__(1024) uint8_t smem[];
  const uint32_t sbase = smem_u32(smem);
  const uint32_t bars = sbase + BAR_OFF;
  const int warp = __shfl_sync(~0u, (int)(threadIdx.x >> 5), 0), lane = threadIdx.x & 31;
  const int crank = blockIdx.x & 1;
  const int cl = blockIdx.x >> 1;
  const int set = cl < 4 ? 15 : (cl < 36 ? ((cl - 4) & 7) : 8 + (cl - 36) % 7);
  const int pos = cl < 4 ? cl : (cl < 36 ? ((cl - 4) >> 3) : (cl - 36) / 7);
  const int j = 4 * (set >> 3) + pos;
  const int rb = 2 * (set & 7) + crank;

  if (threadIdx.x == 256) {
    asm volatile("prefetch.tensormap [%0];" ::"l"(reinterpret_cast<uint64_t>(&prm.tx)) : "memory");
    asm volatile("prefetch.tensormap [%0];" ::"l"(reinterpret_cast<uint64_t>(&prm.tqkv)) : "memory");
#pragma unroll
    for (int i = 0; i < NST; i++) {
      mbar_init(bars + i * 8, 1);
      mbar_init(bars + (NST + i) * 8, 16);
    }
    mbar_init(bars + 16 * 8, 1);
    mbar_init(bars + 22 * 8, 1);
    mbar_init(bars + 23 * 8, 1);
    mbar_init(bars + 24 * 8, 2);
    mbar_init(bars + 25 * 8, 16);
    asm volatile("fence.mbarrier_init.release.cluster;" ::: "memory");
    produce_stage<0>(prm, sbase, bars, rb, j, crank);
    produce_stage<1>(prm, sbase, bars, rb, j, crank);
  }
  __syncthreads();
  asm volatile("barrier.cluster.arrive.relaxed.aligned;\nbarrier.cluster.wait.aligned;" ::: "memory");

  if (warp >= 8) {
    asm volatile("setmaxnreg.dec.sync.aligned.u32 24;");
    if (warp == 8) {
      if (elect_one()) {
        produce_stage<4>(prm, sbase, bars, rb, j, crank);
        produce_stage<5>(prm, sbase, bars, rb, j, crank);
        produce_stage<6>(prm, sbase, bars, rb, j, crank);
        produce_stage<7>(prm, sbase, bars, rb, j, crank);
        produce_stage<8>(prm, sbase, bars, rb, j, crank);
        produce_stage<9>(prm, sbase, bars, rb, j, crank);
        produce_stage<3>(prm, sbase, bars, rb, j, crank);
        produce_stage<2>(prm, sbase, bars, rb, j, crank);
        produce_from<10>(prm, sbase, bars, rb, j, crank);
      }
    } else if (warp == 10) {
      const uint32_t zsrc = sbase + ZERO_OFF;
      for (int i = lane * 16; i < ZERO_B; i += 512) asm volatile("st.shared.v4.b32 [%0], {%1,%1,%1,%1};" ::"r"(zsrc + i), "r"(0) : "memory");
      asm volatile("fence.proxy.async.shared::cta;" ::: "memory");
      __syncwarp();
      mbar_wait(bars + 16 * 8, 0);
      mbar_wait(bars + slot_of(4) * 8, 0);
      if (lane == 0) {
        uint32_t np;
        asm volatile("ld.shared.u32 %0, [%1];" : "=r"(np) : "r"(bars + 17 * 8) : "memory");
        np = (np & 1) ^ 1;
        for (int t = 0; t < 8; t++) bulk_store(g_O[np] + ((rb * 8 + t) * 8 + j) * 112, zsrc, 1792);
        for (int p = 0; p < 2; p++) bulk_store(g_halo[np] + ((rb * 2 + p) * 8 + j) * 128, zsrc, 2048);
        for (int t = 0; t < 8; t++) bulk_store(g_H[np] + ((rb * 8 + t) * 8 + j) * 120, zsrc, 1920);
        asm volatile("cp.async.bulk.commit_group;\ncp.async.bulk.wait_group 0;" ::: "memory");
      }
    }
  } else {
    asm volatile("setmaxnreg.inc.sync.aligned.u32 240;");
    const int p = warp >> 2, w = warp & 3;
    const int r = lane >> 2, q = lane & 3;
    const int tile_id = (rb * 2 + p) * 4 + w;
    const int tok0 = 128 * rb + 32 * w + p + 2 * r;
    const uint32_t pbars = map_to_cta(bars, crank ^ 1);
    const uint32_t dbase0 = ((sbase & 0x3ffffu) >> 4) | DESC_LBO;

    constexpr uint32_t dhi = DESC_HI, dhi_far = DESC_HI_FAR;

    uint32_t* sync = g_sync + tile_id * 64;
    uint32_t epoch, epoch2;
    asm volatile("ld.relaxed.gpu.global.u32 %0, [%1];" : "=r"(epoch) : "l"(sync + lane) : "memory");
    asm volatile("ld.relaxed.gpu.global.u32 %0, [%1];" : "=r"(epoch2) : "l"(sync + 32 + lane) : "memory");

    uint32_t A[112];
    {
      const int xslot = w >> 1;
      const uint32_t tb = sbase + xslot * STAGE_B + (w & 1) * TILE_B;
      mbar_wait(bars + (p == 0 ? xslot : 22 + xslot) * 8, 0);
      const int row = (lane & 7) + ((lane >> 3) & 1) * 8;
      const uint32_t rowa = tb + row * 128;
#pragma unroll
      for (int s = 0; s < 28; s++) {
        const uint32_t unit = 2 * (s & 3) + (lane >> 4);
        const uint32_t addr = rowa + (s >> 2) * 2048 + ((unit ^ (row & 7)) << 4);
        asm volatile("ldmatrix.sync.aligned.m8n8.x4.shared.b16 {%0,%1,%2,%3}, [%4];"
                     : "=r"(A[4 * s]), "=r"(A[4 * s + 1]), "=r"(A[4 * s + 2]), "=r"(A[4 * s + 3])
                     : "r"(addr)
                     : "memory");
      }
      release_stage(bars, pbars, xslot, 4, lane);
      if (p == 1 && w >= 2 && lane == 0) mbar_arrive(bars + 24 * 8, 1);
    }
    epoch = __shfl_sync(~0u, epoch, SY_EPOCH);
    epoch2 = __shfl_sync(~0u, epoch2, SY_EPOCH2 - 32);
    const uint32_t stamp = epoch + 1;
    const int par = epoch & 1;
    const uint32_t tag = (epoch2 & 1) ^ 1;
    if (warp == 0 && lane == 0) {
      asm volatile("st.shared.u32 [%0], %1;" ::"r"(bars + 17 * 8), "r"(epoch) : "memory");
      mbar_arrive(bars + 16 * 8, 1);
    }
    float dm0, dm1;
    uint32_t m0, m1;
    row_means(A, m0, m1, dm0, dm1);
    center_part<0, 7>(A, m0, m1);

    if (p == 1) asm volatile("bar.sync 1, 256;" ::: "memory");
    float akv[60], aq[28];
    float sq[2] = {0.f, 0.f};
#define KV_STAGE(Q)                                                                                         \
    {                                                                                                       \
      wait_stage<4 + Q>(bars);                                                                              \
      const uint32_t dbase = opaque(dbase0);                                                                \
      wg_fence();                                                                                           \
      _Pragma("unroll") for (int ks = 0; ks < 7; ks++) {                                                    \
        const int s = 7 * Q + ks;                                                                           \
        const uint32_t d = dbase + ((slot_of(4 + Q) * STAGE_B + ks * 2048) >> 4);                          \
        if (Q == 0 && ks == 0) wgmma_n120_init(akv, A[4 * s], A[4 * s + 1], A[4 * s + 2], A[4 * s + 3], d, dhi); \
        else wgmma_n120(akv, A[4 * s], A[4 * s + 1], A[4 * s + 2], A[4 * s + 3], d, dhi);                   \
      }                                                                                                     \
      wg_commit();                                                                                          \
      if (Q < 3) center_part<(Q < 3 ? 7 * Q + 7 : 0), 7>(A, m0, m1);                        \
      sumsq_part<7 * Q, 7>(A, sq);                                                                            \
      if (Q > 0) { wg_wait<1>(); release_stage(bars, pbars, slot_of(4 + Q - 1), 1, lane); }                         \
    }
    KV_STAGE(0) KV_STAGE(1) KV_STAGE(2) KV_STAGE(3)
#define Q_STAGE(T)                                                                                          \
    {                                                                                                       \
      wait_stage<8 + T>(bars);                                                                              \
      const uint32_t dbase = opaque(dbase0);                                                                \
      wg_fence();                                                                                           \
      _Pragma("unroll") for (int u = 0; u < 14; u++) {                                                      \
        const int s = 14 * T + u;                                                                           \
        const uint32_t d = dbase + ((slot_of(8 + T) * STAGE_B + (u / 7) * TILE_B + (u % 7) * 2048) >> 4);  \
        if (T == 0 && u == 0) wgmma_n56_init(aq, A[4 * s], A[4 * s + 1], A[4 * s + 2], A[4 * s + 3], d, dhi); \
        else wgmma_n56(aq, A[4 * s], A[4 * s + 1], A[4 * s + 2], A[4 * s + 3], d, dhi);                 \
      }                                                                                                     \
      wg_commit();                                                                                          \
    }
    Q_STAGE(0) Q_STAGE(1)
    if (p == 0) asm volatile("bar.arrive 1, 256;" ::: "memory");
    float rs0, rs1;
    finish_rstd(sq, dm0, dm1, rs0, rs1);
    wg_wait<2>();
    reg_fence(akv);

    uint32_t kb[14], vb[14], kp[7], vp[7];
#pragma unroll
    for (int b = 0; b < 7; b++) {
      kb[2 * b] = pack_bf16(akv[4 * b] * rs0, akv[4 * b + 1] * rs0);
      kb[2 * b + 1] = pack_bf16(akv[4 * b + 2] * rs1, akv[4 * b + 3] * rs1);
      vb[2 * b] = pack_bf16(akv[32 + 4 * b] * rs0, akv[32 + 4 * b + 1] * rs0);
      vb[2 * b + 1] = pack_bf16(akv[32 + 4 * b + 2] * rs1, akv[32 + 4 * b + 3] * rs1);
    }
    if (w < 3) {
      mbar_wait(bars + 24 * 8, 0);
      const uint32_t hb = sbase + HAND_OFF + (p * 3 + w) * 2048 + lane * 16;
      asm volatile("st.shared.v4.b32 [%0], {%1,%2,%3,%4};" ::"r"(hb), "r"(kb[1]), "r"(kb[3]), "r"(kb[5]), "r"(kb[7]) : "memory");
      asm volatile("st.shared.v4.b32 [%0], {%1,%2,%3,%4};" ::"r"(hb + 512), "r"(kb[9]), "r"(kb[11]), "r"(kb[13]), "r"(0) : "memory");
      asm volatile("st.shared.v4.b32 [%0], {%1,%2,%3,%4};" ::"r"(hb + 1024), "r"(vb[1]), "r"(vb[3]), "r"(vb[5]), "r"(vb[7]) : "memory");
      asm volatile("st.shared.v4.b32 [%0], {%1,%2,%3,%4};" ::"r"(hb + 1536), "r"(vb[9]), "r"(vb[11]), "r"(vb[13]), "r"(0) : "memory");
    } else if (rb < 15) {
      char* hp = reinterpret_cast<char*>(g_halo[par] + ((rb * 2 + p) * 8 + j) * 128) + lane * 16;
      stx16(hp, nz(kb[1]), kb[3], kb[5], kb[7]);
      stx16(hp + 512, nz(kb[9]), kb[11], kb[13], 0);
      stx16(hp + 1024, nz(vb[1]), vb[3], vb[5], vb[7]);
      stx16(hp + 1536, nz(vb[9]), vb[11], vb[13], 0);
      post_hint(halo_hint(rb + 1, p, j), stamp, lane);
    }
    release_stage(bars, pbars, slot_of(7), 1, lane);
    asm volatile("bar.sync %0, 128;" ::"r"(2 + p) : "memory");
    if (w > 0) {
      const uint32_t hb = sbase + HAND_OFF + (p * 3 + w - 1) * 2048 + lane * 16;
      [[maybe_unused]] uint32_t z;
      asm volatile("ld.shared.v4.b32 {%0,%1,%2,%3}, [%4];" : "=r"(kp[0]), "=r"(kp[1]), "=r"(kp[2]), "=r"(kp[3]) : "r"(hb) : "memory");
      asm volatile("ld.shared.v4.b32 {%0,%1,%2,%3}, [%4];" : "=r"(kp[4]), "=r"(kp[5]), "=r"(kp[6]), "=r"(z) : "r"(hb + 512) : "memory");
      asm volatile("ld.shared.v4.b32 {%0,%1,%2,%3}, [%4];" : "=r"(vp[0]), "=r"(vp[1]), "=r"(vp[2]), "=r"(vp[3]) : "r"(hb + 1024) : "memory");
      asm volatile("ld.shared.v4.b32 {%0,%1,%2,%3}, [%4];" : "=r"(vp[4]), "=r"(vp[5]), "=r"(vp[6]), "=r"(z) : "r"(hb + 1536) : "memory");
    } else {
#pragma unroll
      for (int b = 0; b < 7; b++) kp[b] = vp[b] = 0;
    }
    release_stage(bars, pbars, 25 - NST, 1, lane);
    if (w == 0 && rb > 0) {
      const char* hp = reinterpret_cast<const char*>(g_halo[par] + (((rb - 1) * 2 + p) * 8 + j) * 128) + lane * 16;
      wait_hint(halo_hint(rb, p, j), stamp);
      uint4 u0, u1, u2, u3;
      uint32_t it = 0;
#pragma unroll 1
      while (true) {
        u0 = ldx16(hp); u1 = ldx16(hp + 512); u2 = ldx16(hp + 1024); u3 = ldx16(hp + 1536);
        if (__all_sync(~0u, u0.x != 0 && u1.x != 0 && u2.x != 0 && u3.x != 0) || spin_expired(it)) break;
      }
      kp[0] = u0.x; kp[1] = u0.y; kp[2] = u0.z; kp[3] = u0.w; kp[4] = u1.x; kp[5] = u1.y; kp[6] = u1.z;
      vp[0] = u2.x; vp[1] = u2.y; vp[2] = u2.z; vp[3] = u2.w; vp[4] = u3.x; vp[5] = u3.y; vp[6] = u3.z;
    }
    const bool has_prev = (w > 0) || (rb > 0);
    uint32_t vt[21];
#pragma unroll
    for (int b = 0; b < 7; b++) {
      vt[3 * b] = movmat(vp[b]);
      vt[3 * b + 1] = movmat(vb[2 * b]);
      vt[3 * b + 2] = movmat(vb[2 * b + 1]);
    }

    wg_wait<0>();
    reg_fence(aq);
    release_stage(bars, pbars, slot_of(8), 1, lane);
    release_stage(bars, pbars, slot_of(9), 1, lane);
    uint32_t xr[14];
    {
      const uint32_t* xp = reinterpret_cast<const uint32_t*>(x + (size_t)tok0 * DM + 56 * j + 2 * q);
#pragma unroll
      for (int b = 0; b < 7; b++) {
        asm volatile("ld.global.nc.b32 %0, [%1];" : "=r"(xr[2 * b]) : "l"(xp + 4 * b));
        asm volatile("ld.global.nc.b32 %0, [%1];" : "=r"(xr[2 * b + 1]) : "l"(xp + 4 * b + 16 * DM / 2));
      }
    }

    uint32_t ob[14];
    {
      uint32_t qb[14];
#pragma unroll
      for (int b = 0; b < 7; b++) {
        qb[2 * b] = pack_bf16(aq[4 * b] * rs0, aq[4 * b + 1] * rs0);
        qb[2 * b + 1] = pack_bf16(aq[4 * b + 2] * rs1, aq[4 * b + 3] * rs1);
      }
      const float sc = 0.18898223650461362f * 1.4426950408889634f;
      const bool l0 = 2 * q > r, l1 = 2 * q + 1 > r;
      float sa[2][2][3][4];
#pragma unroll
      for (int h = 0; h < 2; h++) {
        const int b0 = h == 0 ? 0 : 3;
        const bool keep3 = h == 0 ? (q < 2) : (q >= 2);
#pragma unroll
        for (int ks = 0; ks < 2; ks++) {
          const int ba = b0 + 2 * ks, bb = ba + 1;
          uint32_t a0 = qb[2 * ba], a1 = qb[2 * ba + 1], a2 = qb[2 * bb], a3 = qb[2 * bb + 1];
          if (ba == 3 && h == 1) { a0 = keep3 ? a0 : 0u; a1 = keep3 ? a1 : 0u; }
          if (bb == 3 && h == 0) { a2 = keep3 ? a2 : 0u; a3 = keep3 ? a3 : 0u; }
#pragma unroll
          for (int t = 0; t < 3; t++) sa[h][ks][t][0] = sa[h][ks][t][1] = sa[h][ks][t][2] = sa[h][ks][t][3] = 0.f;
          mma16816(sa[h][ks][0], a0, a1, a2, a3, kp[ba], kp[bb]);
          mma16816(sa[h][ks][1], a0, a1, a2, a3, kb[2 * ba], kb[2 * bb]);
          mma16816(sa[h][ks][2], a0, a1, a2, a3, kb[2 * ba + 1], kb[2 * bb + 1]);
        }
      }
      uint32_t pa[2][4];
#pragma unroll
      for (int h = 0; h < 2; h++) {
        const float NEG = -INFINITY;
        float x00 = l0 ? sa[h][0][0][0] + sa[h][1][0][0] : sa[h][0][1][0] + sa[h][1][1][0];
        float x01 = l1 ? sa[h][0][0][1] + sa[h][1][0][1] : sa[h][0][1][1] + sa[h][1][1][1];
        float x10 = l0 ? sa[h][0][1][2] + sa[h][1][1][2] : sa[h][0][2][2] + sa[h][1][2][2];
        float x11 = l1 ? sa[h][0][1][3] + sa[h][1][1][3] : sa[h][0][2][3] + sa[h][1][2][3];
        x00 = (l0 && !has_prev) ? NEG : x00 * sc;
        x01 = (l1 && !has_prev) ? NEG : x01 * sc;
        x10 *= sc; x11 *= sc;
        float m0 = fmaxf(x00, x01), m1 = fmaxf(x10, x11);
        m0 = fmaxf(m0, __shfl_xor_sync(~0u, m0, 1));
        m1 = fmaxf(m1, __shfl_xor_sync(~0u, m1, 1));
        m0 = fmaxf(m0, __shfl_xor_sync(~0u, m0, 2));
        m1 = fmaxf(m1, __shfl_xor_sync(~0u, m1, 2));
        float p00 = ex2(x00 - m0), p01 = ex2(x01 - m0), p10 = ex2(x10 - m1), p11 = ex2(x11 - m1);
        float t0 = p00 + p01, t1 = p10 + p11;
        t0 += __shfl_xor_sync(~0u, t0, 1);
        t1 += __shfl_xor_sync(~0u, t1, 1);
        t0 += __shfl_xor_sync(~0u, t0, 2);
        t1 += __shfl_xor_sync(~0u, t1, 2);
        const float i0 = rcp(t0), i1 = rcp(t1);
        p00 *= i0; p01 *= i0; p10 *= i1; p11 *= i1;
        pa[h][0] = pack_bf16(l0 ? p00 : 0.f, l1 ? p01 : 0.f);
        pa[h][1] = pack_bf16(l0 ? 0.f : p00, l1 ? 0.f : p01);
        pa[h][2] = pack_bf16(l0 ? p10 : 0.f, l1 ? p11 : 0.f);
        pa[h][3] = pack_bf16(l0 ? 0.f : p10, l1 ? 0.f : p11);
      }
      float oacc[2][4][4], oex[2][4][4];
#pragma unroll
      for (int h = 0; h < 2; h++) {
#pragma unroll
        for (int u = 0; u < 4; u++) {
          const int b = (h == 0 ? 0 : 3) + u;
          oacc[h][u][0] = oacc[h][u][1] = oacc[h][u][2] = oacc[h][u][3] = 0.f;
          oex[h][u][0] = oex[h][u][1] = oex[h][u][2] = oex[h][u][3] = 0.f;
          mma16816(oacc[h][u], pa[h][0], 0u, pa[h][1], pa[h][2], vt[3 * b], vt[3 * b + 1]);
          mma1688(oex[h][u], 0u, pa[h][3], vt[3 * b + 2]);
        }
      }
#pragma unroll
      for (int h = 0; h < 2; h++)
#pragma unroll
        for (int u = 0; u < 4; u++) { oacc[h][u][2] += oex[h][u][2]; oacc[h][u][3] += oex[h][u][3]; }
#pragma unroll
      for (int b = 0; b < 7; b++) {
        float o0, o1, o2, o3;
        if (b < 3) { o0 = oacc[0][b][0]; o1 = oacc[0][b][1]; o2 = oacc[0][b][2]; o3 = oacc[0][b][3]; }
        else if (b > 3) { o0 = oacc[1][b - 3][0]; o1 = oacc[1][b - 3][1]; o2 = oacc[1][b - 3][2]; o3 = oacc[1][b - 3][3]; }
        else {
          const bool h0 = q < 2;
          o0 = h0 ? oacc[0][3][0] : oacc[1][0][0]; o1 = h0 ? oacc[0][3][1] : oacc[1][0][1];
          o2 = h0 ? oacc[0][3][2] : oacc[1][0][2]; o3 = h0 ? oacc[0][3][3] : oacc[1][0][3];
        }
        ob[2 * b] = pack_bf16(o0, o1);
        ob[2 * b + 1] = pack_bf16(o2, o3);
      }
    }
    store_slice(g_O[par] + (tile_id * 8 + j) * 112, ob, lane);
    post_hint(sync + SY_O + j, stamp, lane);

    const char* otile = reinterpret_cast<const char*>(g_O[par] + tile_id * 8 * 112);
    wait_hint(sync + SY_O + (lane & 7), stamp);
    load_xtile<0, 1792>(A, otile, lane);
    load_xtile<1, 1792>(A, otile, lane);
    load_xtile<2, 1792>(A, otile, lane);
    load_xtile<3, 1792>(A, otile, lane);
    float ah[28];
#define X_STEP(ACC, FN, T, KS, ADDR, FIRST)                                                                   \
    if (FIRST) FN##_init(ACC, A[28 * T + 4 * KS], A[28 * T + 4 * KS + 1], A[28 * T + 4 * KS + 2], A[28 * T + 4 * KS + 3], \
                         dbase + (((ADDR) + xoff<KS>()) >> 4), KS == 3 ? dhi_far : dhi);                      \
    else FN(ACC, A[28 * T + 4 * KS], A[28 * T + 4 * KS + 1], A[28 * T + 4 * KS + 2], A[28 * T + 4 * KS + 3],  \
            dbase + (((ADDR) + xoff<KS>()) >> 4), KS == 3 ? dhi_far : dhi);
#define X_TILE(ACC, FN, T, ADDR, FIRST)                                                                       \
    { const uint32_t dbase = opaque(dbase0); wg_fence();                                                      \
    X_STEP(ACC, FN, T, 0, ADDR, FIRST) X_STEP(ACC, FN, T, 1, ADDR, false) X_STEP(ACC, FN, T, 2, ADDR, false)   \
    X_STEP(ACC, FN, T, 3, ADDR, false) X_STEP(ACC, FN, T, 4, ADDR, false) X_STEP(ACC, FN, T, 5, ADDR, false)   \
    X_STEP(ACC, FN, T, 6, ADDR, false) }
    wait_stage<10>(bars);
    check_xtile<0, 1792>(A, otile, lane);
    X_TILE(ah, wgmma_n56, 0, slot_of(10) * STAGE_B, true)
    wg_commit();
    check_xtile<1, 1792>(A, otile, lane);
    X_TILE(ah, wgmma_n56, 1, slot_of(10) * STAGE_B + TILE_B, false)
    wg_commit();
    wait_stage<11>(bars);
    check_xtile<2, 1792>(A, otile, lane);
    X_TILE(ah, wgmma_n56, 2, slot_of(11) * STAGE_B, false)
    wg_commit();
    check_xtile<3, 1792>(A, otile, lane);
    X_TILE(ah, wgmma_n56, 3, slot_of(11) * STAGE_B + TILE_B, false)
    wg_commit();
    wg_wait<2>();
    release_stage(bars, pbars, slot_of(10), 1, lane);
    wg_wait<0>();
    reg_fence(ah);
    {
      uint32_t hb[14];
#pragma unroll
      for (int b = 0; b < 7; b++) {
        hb[2 * b] = bf2_add(xr[2 * b], pack_bf16(ah[4 * b], ah[4 * b + 1]));
        hb[2 * b + 1] = bf2_add(xr[2 * b + 1], pack_bf16(ah[4 * b + 2], ah[4 * b + 3]));
      }
      store_slice(g_H[par] + (tile_id * 8 + j) * 120, hb, lane);
      uint32_t d[14];
#pragma unroll
      for (int i = 0; i < 14; i++) d[i] = bf2_sub(hb[i], (i & 1) ? m1 : m0);
      float s0 = 0.f, s1 = 0.f, q0 = 0.f, q1 = 0.f;
#pragma unroll
      for (int b = 0; b < 7; b++) {
        const float a = bf_lo(d[2 * b]), c = bf_hi(d[2 * b]), e = bf_lo(d[2 * b + 1]), f = bf_hi(d[2 * b + 1]);
        s0 += a + c; q0 = fmaf(a, a, fmaf(c, c, q0));
        s1 += e + f; q1 = fmaf(e, e, fmaf(f, f, q1));
      }
#pragma unroll
      for (int o = 1; o < 4; o <<= 1) {
        s0 += __shfl_xor_sync(~0u, s0, o); q0 += __shfl_xor_sync(~0u, q0, o);
        s1 += __shfl_xor_sync(~0u, s1, o); q1 += __shfl_xor_sync(~0u, q1, o);
      }
      if (q < 2) {
        char* sp = reinterpret_cast<char*>(g_H[par] + (tile_id * 8 + j) * 120) + 1792 + (r + 8 * q) * 8;
        stx8(sp, __float_as_uint(q ? s1 : s0) | 1u, __float_as_uint(q ? q1 : q0));
      }
      post_hint(sync + SY_H + j, stamp, lane);
      release_stage(bars, pbars, slot_of(11), 1, lane);
    }

    const char* htile = reinterpret_cast<const char*>(g_H[par] + tile_id * 8 * 120);
    {
      wait_hint(sync + SY_H + (lane & 7), stamp);
      const char* sp = htile + q * 3840 + 1792 + r * 8;
      uint2 ua = ldx8(sp), ub = ldx8(sp + 1920), uc = ldx8(sp + 64), ud = ldx8(sp + 1920 + 64);
      load_xtile<0, 1920>(A, htile, lane);
      load_xtile<1, 1920>(A, htile, lane);
      load_xtile<2, 1920>(A, htile, lane);
      load_xtile<3, 1920>(A, htile, lane);
      if (__builtin_expect(!__all_sync(~0u, min(min(ua.x, ub.x), min(uc.x, ud.x)) != 0), 0)) {
        uint32_t it = 0;
#pragma unroll 1
        do {
          ua = ldx8(sp); ub = ldx8(sp + 1920); uc = ldx8(sp + 64); ud = ldx8(sp + 1920 + 64);
        } while (!__all_sync(~0u, min(min(ua.x, ub.x), min(uc.x, ud.x)) != 0) && !spin_expired(it));
      }
      float s0 = __uint_as_float(ua.x) + __uint_as_float(ub.x), q0 = __uint_as_float(ua.y) + __uint_as_float(ub.y);
      float s1 = __uint_as_float(uc.x) + __uint_as_float(ud.x), q1 = __uint_as_float(uc.y) + __uint_as_float(ud.y);
#pragma unroll
      for (int o = 1; o < 4; o <<= 1) {
        s0 += __shfl_xor_sync(~0u, s0, o); q0 += __shfl_xor_sync(~0u, q0, o);
        s1 += __shfl_xor_sync(~0u, s1, o); q1 += __shfl_xor_sync(~0u, q1, o);
      }
      s0 *= 1.f / DM; s1 *= 1.f / DM;
      rs0 = rstd_of(q0, s0);
      rs1 = rstd_of(q1, s1);
      const float mu0 = bf_lo(m0) + s0, mu1 = bf_lo(m1) + s1;
      m0 = pack_bf16(mu0, mu0);
      m1 = pack_bf16(mu1, mu1);
    }
    uint32_t H1[56];
    {
      float a1[64];
#define CENTER_TILE(T)                                                                                        \
      check_xtile<T, 1920>(A, htile, lane);                                                                         \
      _Pragma("unroll") for (int i = 0; i < 28; i++) A[28 * T + i] = bf2_sub(A[28 * T + i], (i & 1) ? m1 : m0);
#define W1_STAGE(ACC, FN, IDX, T)                                                                             \
      wait_stage<IDX>(bars);                                                                                  \
      X_TILE(ACC, FN, T, slot_of(IDX) * STAGE_B, T == 0)                                                       \
      wg_commit();                                                                                            \
      if (T > 0) { wg_wait<1>(); release_stage(bars, pbars, slot_of(IDX - 1), 1, lane); }
      CENTER_TILE(0) W1_STAGE(a1, wgmma_n128, 12, 0)
      CENTER_TILE(1) W1_STAGE(a1, wgmma_n128, 13, 1)
      CENTER_TILE(2) W1_STAGE(a1, wgmma_n128, 14, 2)
      CENTER_TILE(3)
      W1_STAGE(a1, wgmma_n128, 15, 3)
      wg_wait<0>();
      reg_fence(a1);
      release_stage(bars, pbars, slot_of(15), 1, lane);
#pragma unroll
      for (int b = 0; b < 16; b++) {
        H1[2 * b] = pack_bf16_relu(a1[4 * b] * rs0, a1[4 * b + 1] * rs0);
        H1[2 * b + 1] = pack_bf16_relu(a1[4 * b + 2] * rs1, a1[4 * b + 3] * rs1);
      }
    }
    {
      float a2[48];
      W1_STAGE(a2, wgmma_n96, 16, 0)
      W1_STAGE(a2, wgmma_n96, 17, 1)
      W1_STAGE(a2, wgmma_n96, 18, 2)
      W1_STAGE(a2, wgmma_n96, 19, 3)
      wg_wait<0>();
      reg_fence(a2);
#pragma unroll
      for (int b = 0; b < 12; b++) {
        H1[32 + 2 * b] = pack_bf16_relu(a2[4 * b] * rs0, a2[4 * b + 1] * rs0);
        H1[32 + 2 * b + 1] = pack_bf16_relu(a2[4 * b + 2] * rs1, a2[4 * b + 3] * rs1);
      }
    }

    __nv_bfloat16* orow = out + (size_t)tok0 * DM;
    const uint32_t eye = (r == 2 * q ? 0x00003f80u : 0u) | (r == 2 * q + 1 ? 0x3f800000u : 0u);

#define W2_HALF(ACC, IDX, KH)                                                                                 \
    wait_stage<IDX>(bars);                                                                                    \
    wg_fence();                                                                                               \
    _Pragma("unroll") for (int ks = 0; ks < 7; ks++) {                                                        \
      const int s = 7 * KH + ks;                                                                              \
      const uint32_t d = opaque(dbase0) + ((slot_of(IDX) * STAGE_B + ks * 2048) >> 4);                                  \
      if (KH == 0 && ks == 0) wgmma_n128_init(ACC, H1[4 * s], H1[4 * s + 1], H1[4 * s + 2], H1[4 * s + 3], d, dhi); \
      else wgmma_n128(ACC, H1[4 * s], H1[4 * s + 1], H1[4 * s + 2], H1[4 * s + 3], d, dhi);               \
    }                                                                                                         \
    wg_commit();
#define P_STORE_PART(ACC, C, O0, O1)                                                                          \
    {                                                                                                         \
      uint4* pp = g_P + (tile_id * 8 + j) * 896 + C * 256 + lane;                                             \
      _Pragma("unroll") for (int o = O0; o < O1; o++)                                                         \
        stx16(pp + o * 32, (pack_bf16(ACC[8 * o], ACC[8 * o + 1]) & ~1u) | tag, pack_bf16(ACC[8 * o + 2], ACC[8 * o + 3]), \
              pack_bf16(ACC[8 * o + 4], ACC[8 * o + 5]), pack_bf16(ACC[8 * o + 6], ACC[8 * o + 7]));          \
    }
#define P_STORE(ACC, C) P_STORE_PART(ACC, C, 0, 8)
    const uint4* pp = g_P + tile_id * 8 * 896 + j * 32 + lane;
    const uint2* p3 = reinterpret_cast<const uint2*>(g_P + tile_id * 8 * 896 + 512) + j * 32 + lane;
    uint4 v0[8], v1[8];
    uint2 hr[10];
#define W2_NARROW(ACC, IDX)                                                                                   \
    wait_stage<IDX>(bars);                                                                                    \
    wg_fence();                                                                                               \
    _Pragma("unroll") for (int s = 0; s < 14; s++) {                                                          \
      const uint32_t d = opaque(dbase0) + ((slot_of(IDX) * STAGE_B + (s / 7) * TILE_B + (s % 7) * 2048) >> 4); \
      if (s == 0) wgmma_n64_init(ACC, H1[4 * s], H1[4 * s + 1], H1[4 * s + 2], H1[4 * s + 3], d, dhi);        \
      else wgmma_n64(ACC, H1[4 * s], H1[4 * s + 1], H1[4 * s + 2], H1[4 * s + 3], d, dhi);                    \
    }                                                                                                         \
    wg_commit();
#define P_STORE_NARROW(ACC, C)                                                                                \
    {                                                                                                         \
      uint2* ps = reinterpret_cast<uint2*>(g_P + (tile_id * 8 + j) * 896 + 512) + C * 256 + lane;             \
      _Pragma("unroll") for (int o = 0; o < 8; o++) {                                                         \
        const int ba = 2 * (o >> 1), hf = o & 1;                                                              \
        stx8(ps + o * 32, (pack_bf16(ACC[4 * ba + 2 * hf], ACC[4 * ba + 2 * hf + 1]) & ~1u) | tag,            \
             pack_bf16(ACC[4 * (ba + 1) + 2 * hf], ACC[4 * (ba + 1) + 2 * hf + 1]));                          \
      }                                                                                                       \
    }
    {
      float b0[64], b1[64];
      W2_HALF(b0, 20, 0)
      W2_HALF(b0, 21, 1)
      W2_HALF(b1, 22, 0)
      wg_wait<1>();
      reg_fence(b0);
      W2_HALF(b1, 23, 1)
      float c0[32], c1[32], c2[32];
      P_STORE(b0, 0)
      W2_NARROW(c0, 24)
      wg_wait<1>();
      reg_fence(b1);
      W2_NARROW(c1, 25)
      P_STORE(b1, 1)
#pragma unroll
      for (int c = 0; c < 2; c++) {
        hr[2 * c] = load_h_block(htile, 16 * c + 2 * j, lane);
        hr[2 * c + 1] = load_h_block(htile, 16 * c + 2 * j + 1, lane);
      }
#pragma unroll
      for (int c = 0; c < 3; c++) {
        hr[4 + 2 * c] = load_h_block(htile, 32 + 8 * c + 2 * (j >> 1), lane);
        hr[5 + 2 * c] = load_h_block(htile, 32 + 8 * c + 2 * (j >> 1) + 1, lane);
      }
      wg_wait<1>();
      reg_fence(c0);
      W2_NARROW(c2, 26)
      P_STORE_NARROW(c0, 0)
      wg_wait<1>();
      reg_fence(c1);
      P_STORE_NARROW(c1, 1)
      wg_wait<0>();
      reg_fence(c2);
      P_STORE_NARROW(c2, 2)
      post_hint(sync + SY_P3 + j, stamp, lane);
    }
    {
      const int hf = j & 1;
      const bool odd = q & 1;
      const int coff = odd ? 8 + 2 * (q - 1) : 2 * q;
#define P_BAD(V) ((V[0].x ^ tag) | (V[1].x ^ tag) | (V[2].x ^ tag) | (V[3].x ^ tag) | (V[4].x ^ tag) | (V[5].x ^ tag) | (V[6].x ^ tag) | (V[7].x ^ tag))
#define P_CHECK(V, OFF)                                                                                       \
      if (__builtin_expect(!__all_sync(~0u, (P_BAD(V) & 1) == 0), 0)) {                                       \
        uint32_t it = 0;                                                                                      \
        _Pragma("unroll 1") do {                                                                              \
          _Pragma("unroll") for (int s = 0; s < 8; s++) V[s] = ldx16(pp + OFF + s * 896);                     \
        } while (!__all_sync(~0u, (P_BAD(V) & 1) == 0) && !spin_expired(it));                                 \
      }
#define P_FINISH(V, C)                                                                                        \
      {                                                                                                       \
        float fa[2][4] = {{0.f, 0.f, 0.f, 0.f}, {0.f, 0.f, 0.f, 0.f}}, fb[2][4] = {{0.f, 0.f, 0.f, 0.f}, {0.f, 0.f, 0.f, 0.f}}; \
        _Pragma("unroll") for (int s = 0; s < 8; s++) {                                                       \
          mma1688(fa[s & 1], V[s].x, V[s].y, eye);                                                            \
          mma1688(fb[s & 1], V[s].z, V[s].w, eye);                                                            \
        }                                                                                                     \
        const uint32_t oa0 = bf2_add(hr[2 * C].x, pack_bf16(fa[0][0] + fa[1][0], fa[0][1] + fa[1][1]));       \
        const uint32_t oa1 = bf2_add(hr[2 * C].y, pack_bf16(fa[0][2] + fa[1][2], fa[0][3] + fa[1][3]));       \
        const uint32_t ob0 = bf2_add(hr[2 * C + 1].x, pack_bf16(fb[0][0] + fb[1][0], fb[0][1] + fb[1][1]));   \
        const uint32_t ob1 = bf2_add(hr[2 * C + 1].y, pack_bf16(fb[0][2] + fb[1][2], fb[0][3] + fb[1][3]));   \
        const uint32_t g0 = __shfl_xor_sync(~0u, odd ? oa0 : ob0, 1), g1 = __shfl_xor_sync(~0u, odd ? oa1 : ob1, 1); \
        const int col = 128 * C + 16 * j + coff;                                                              \
        *reinterpret_cast<uint2*>(orow + col) = odd ? make_uint2(g0, ob0) : make_uint2(oa0, g0);              \
        *reinterpret_cast<uint2*>(orow + 16 * DM + col) = odd ? make_uint2(g1, ob1) : make_uint2(oa1, g1);    \
      }
#pragma unroll
      for (int s = 0; s < 8; s++) { v0[s] = ldx16(pp + s * 896); v1[s] = ldx16(pp + 256 + s * 896); }
      wait_hint(sync + SY_P3 + (lane & 7), stamp);
      uint2 v3[3][8];
#pragma unroll
      for (int s = 0; s < 8; s++)
#pragma unroll
        for (int c = 0; c < 3; c++) v3[c][s] = ldx8(p3 + c * 256 + s * 1792);
      if (j == 0 && lane < 2) asm volatile("st.relaxed.gpu.global.u32 [%0], %1;" ::"l"(sync + (lane ? SY_EPOCH2 : SY_EPOCH)), "r"(stamp) : "memory");
      P_CHECK(v0, 0)
      P_FINISH(v0, 0)
      P_CHECK(v1, 256)
      P_FINISH(v1, 1)
      if (__builtin_expect(!__all_sync(~0u, ((P_BAD(v3[0]) | P_BAD(v3[1]) | P_BAD(v3[2])) & 1) == 0), 0)) {
        uint32_t it = 0;
#pragma unroll 1
        do {
#pragma unroll
          for (int s = 0; s < 8; s++)
#pragma unroll
            for (int c = 0; c < 3; c++) v3[c][s] = ldx8(p3 + c * 256 + s * 1792);
        } while (!__all_sync(~0u, ((P_BAD(v3[0]) | P_BAD(v3[1]) | P_BAD(v3[2])) & 1) == 0) && !spin_expired(it));
      }
#pragma unroll
      for (int c = 0; c < 3; c++) {
        float f[2][4] = {{0.f, 0.f, 0.f, 0.f}, {0.f, 0.f, 0.f, 0.f}};
#pragma unroll
        for (int s = 0; s < 8; s++) mma1688(f[s & 1], v3[c][s].x, v3[c][s].y, eye);
        const uint32_t oa = bf2_add(hf ? hr[4 + 2 * c].y : hr[4 + 2 * c].x, pack_bf16(f[0][0] + f[1][0], f[0][1] + f[1][1]));
        const uint32_t ob2 = bf2_add(hf ? hr[5 + 2 * c].y : hr[5 + 2 * c].x, pack_bf16(f[0][2] + f[1][2], f[0][3] + f[1][3]));
        const uint32_t g = __shfl_xor_sync(~0u, odd ? oa : ob2, 1);
        const int col = 256 + 64 * c + 16 * (j >> 1) + coff;
        *reinterpret_cast<uint2*>(orow + hf * 16 * DM + col) = odd ? make_uint2(g, ob2) : make_uint2(oa, g);
      }
    }
  }
  asm volatile("barrier.cluster.arrive.relaxed.aligned;\nbarrier.cluster.wait.aligned;" ::: "memory");
}

typedef CUresult (*EncodeFn)(CUtensorMap*, CUtensorMapDataType, cuuint32_t, void*, const cuuint64_t*, const cuuint64_t*,
                             const cuuint32_t*, const cuuint32_t*, CUtensorMapInterleave, CUtensorMapSwizzle,
                             CUtensorMapL2promotion, CUtensorMapFloatOOBfill);

int encode(EncodeFn fn, CUtensorMap* m, int rank, const void* ptr, const cuuint64_t* dims, const cuuint64_t* strides,
           const cuuint32_t* box) {
  const cuuint32_t es[5] = {1, 1, 1, 1, 1};
  return (int)fn(m, CU_TENSOR_MAP_DATA_TYPE_BFLOAT16, rank, const_cast<void*>(ptr), dims, strides, box, es,
                 CU_TENSOR_MAP_INTERLEAVE_NONE, CU_TENSOR_MAP_SWIZZLE_128B, CU_TENSOR_MAP_L2_PROMOTION_L2_256B,
                 CU_TENSOR_MAP_FLOAT_OOB_FILL_NONE);
}

}

extern "C" void kernel_launch(void* const* d_in, const int* in_sizes, int n_in, void* d_out, int out_size) {
  (void)in_sizes; (void)n_in; (void)out_size;
  static EncodeFn fn = nullptr;
  if (!fn) {
    void* sym = nullptr;
    cudaDriverEntryPointQueryResult st;
    cudaGetDriverEntryPoint("cuTensorMapEncodeTiled", &sym, cudaEnableDefault, &st);
    fn = reinterpret_cast<EncodeFn>(sym);
    cudaFuncSetAttribute(fused_block_kernel, cudaFuncAttributeMaxDynamicSharedMemorySize, SMEM_B);
  }
  Params prm;
  int rc = 0;
  {
    const cuuint64_t dims[4] = {64, SEQ / 2, 7, 2};
    const cuuint64_t str[3] = {2 * DM * 2, 128, DM * 2};
    const cuuint32_t box[4] = {64, 16, 7, 1};
    rc |= encode(fn, &prm.tx, 4, d_in[0], dims, str, box);
  }
  {
    const cuuint64_t dims[2] = {3 * DM, DM};
    const cuuint64_t str[1] = {3 * DM * 2};
    const cuuint32_t box[2] = {56, 112};
    rc |= encode(fn, &prm.tqkv, 2, d_in[1], dims, str, box);
  }
  {
    const cuuint64_t dims[2] = {DM, DM};
    const cuuint64_t str[1] = {DM * 2};
    const cuuint32_t box[2] = {56, 112};
    rc |= encode(fn, &prm.two, 2, d_in[2], dims, str, box);
  }
  {
    const cuuint64_t dims[2] = {DFF, DM};
    const cuuint64_t str[1] = {DFF * 2};
    const cuuint32_t box[2] = {64, 112};
    rc |= encode(fn, &prm.tw1, 2, d_in[4], dims, str, box);
    const cuuint32_t narrow[2] = {32, 112};
    rc |= encode(fn, &prm.tw1n, 2, d_in[4], dims, str, narrow);
  }
  {
    const cuuint64_t dims[2] = {DM, DFF};
    const cuuint64_t str[1] = {DM * 2};
    const cuuint32_t box[2] = {64, 112};
    rc |= encode(fn, &prm.tw2, 2, d_in[5], dims, str, box);
  }
  (void)rc;

  cudaLaunchConfig_t cfg = {};
  cfg.gridDim = dim3(128);
  cfg.blockDim = dim3(NTHREADS);
  cfg.dynamicSmemBytes = SMEM_B;
  cfg.stream = cudaStreamPerThread;
  cudaLaunchAttribute at[1];
  at[0].id = cudaLaunchAttributeClusterDimension;
  at[0].val.clusterDim.x = 2;
  at[0].val.clusterDim.y = 1;
  at[0].val.clusterDim.z = 1;
  cfg.attrs = at;
  cfg.numAttrs = 1;
  cudaLaunchKernelEx(&cfg, fused_block_kernel, prm, reinterpret_cast<const __nv_bfloat16*>(d_in[0]),
                     reinterpret_cast<__nv_bfloat16*>(d_out));
}
```
